```python
import torch

def _softmax(x, axis=-1):
    return torch.softmax(x, dim=axis)

def _gelu(x):
    return torch.nn.functional.gelu(x, approximate='tanh')

def _silu(x):
    return torch.nn.functional.silu(x)

def _sigmoid(x):
    return torch.sigmoid(x)

def _layernorm(x, axis=-1, eps=1e-05):
    m = x.mean(dim=axis, keepdim=True)
    v = x.var(dim=axis, keepdim=True, unbiased=False)
    return (x - m) / torch.sqrt(v + eps)

def _scatter_add(tgt, idx, src, axis=0):
    return tgt.clone().index_add_(axis, idx, src)

def _segment_sum(src, seg, n):
    out = torch.zeros((n,) + src.shape[1:], dtype=src.dtype)
    return out.index_add_(0, seg, src)

def _pad(x, pw):
    flat = tuple((v for pair in reversed(pw) for v in pair))
    return torch.nn.functional.pad(x, flat)
kernel_name = 'concat_heads__mha_block__memory_aug_recurrent_mem_tr__prompt'

def setup_inputs():

    _w = lambda a: (lambda t: t.to(torch.bfloat16) if t.is_floating_point() else t)(torch.as_tensor(a))

    def _A_setup():
        B, S, D, H = (1, 2048, 512, 32)
        return {'x': _w((lambda *s: torch.randn(*s, dtype=torch.bfloat16) * 0.2)(B, S, D)), 'wqkv': _w((lambda *s: torch.randn(*s, dtype=torch.bfloat16) * 0.2)(D, 3 * D)), 'wo': _w((lambda *s: torch.randn(*s, dtype=torch.bfloat16) * 0.05)(D, D))}
    _A_in = _A_setup()

    def _B_setup():
        B, S, Dm = (1, 2048, 512)
        H, Dh = (32, 128)
        M, seg = (8, 32)
        seg = min(seg, S)
        S = S // seg * seg
        return {'x': _w((lambda *s: torch.randn(*s, dtype=torch.bfloat16) * 0.05)(B, S, Dm)), 'mem0': _w((lambda *s: torch.randn(*s, dtype=torch.bfloat16) * 0.8)(B, M, Dm)), 'Wq': _w((lambda *s: torch.randn(*s, dtype=torch.bfloat16) * 1.6)(Dm, H, Dh) * Dm ** (-0.5)), 'Wk': _w((lambda *s: torch.randn(*s, dtype=torch.bfloat16) * 1.6)(Dm, H, Dh) * Dm ** (-0.5)), 'Wv': _w((lambda *s: torch.randn(*s, dtype=torch.bfloat16) * 0.8)(Dm, H, Dh) * Dm ** (-0.5)), 'Wo': _w((lambda *s: torch.randn(*s, dtype=torch.bfloat16) * 0.8)(H, Dh, Dm) * (H * Dh) ** (-0.5)), 'seg_len': seg}
    _B_in = _B_setup()
    return {'A_x': _A_in['x'], 'A_wqkv': _A_in['wqkv'], 'A_wo': _A_in['wo'], 'B_x': _B_in['x'], 'B_mem0': _B_in['mem0'], 'B_Wq': _B_in['Wq'], 'B_Wk': _B_in['Wk'], 'B_Wv': _B_in['Wv'], 'B_Wo': _B_in['Wo'], 'B_seg_len': _B_in['seg_len']}

def reference(A_x, A_wqkv, A_wo, B_x, B_mem0, B_Wq, B_Wk, B_Wv, B_Wo, B_seg_len):

    def _A_ref(x, wqkv, wo):
        B, S, D = x.shape
        H = 32
        Dh = D // H
        qkv = (lambda x, *d: x.permute(*d))((x @ wqkv).reshape(B, S, 3, H, Dh), 2, 0, 3, 1, 4)
        q, k, v = (qkv[0], qkv[1], qkv[2])
        scores = torch.einsum('bhqd,bhkd->bhqk', q, k) * Dh ** (-0.5)
        p = _softmax(scores, axis=-1)
        o = torch.einsum('bhqk,bhkd->bhqd', p, v)
        return (lambda x, *d: x.permute(*d))(o, 0, 2, 1, 3).reshape(B, S, D) @ wo

    def _B_ref(x, mem0, Wq, Wk, Wv, Wo, seg_len):
        B, S, Dm = x.shape
        H, Dh = (Wq.shape[1], Wq.shape[2])
        M = mem0.shape[1]
        scale = Dh ** (-0.5)
        n_seg = S // seg_len
        L = M + seg_len
        idx = torch.arange(L)
        mask = (idx[:, None] < M) | (idx[:, None] >= idx[None, :])
        mem = mem0
        outs = []
        for s in range(n_seg):
            xs = x[:, s * seg_len:(s + 1) * seg_len, :].clone()
            h = torch.concatenate([mem, xs], axis=1)
            q = torch.einsum('btd,dhe->bhte', h, Wq)
            k = torch.einsum('btd,dhe->bhte', h, Wk)
            v = torch.einsum('btd,dhe->bhte', h, Wv)
            scores = torch.einsum('bhqe,bhke->bhqk', q, k) * scale
            scores = torch.where(mask[None, None], scores, -1000000000.0)
            p = _softmax(scores, axis=-1)
            o = torch.einsum('bhqk,bhke->bhqe', p, v)
            o = torch.einsum('bhte,hed->btd', o, Wo)
            mem = o[:, :M, :].clone()
            outs.append(o[:, M:, :])
        return torch.concatenate(outs, axis=1)
    a = _A_ref(A_x, A_wqkv, A_wo)
    b = _B_ref(B_x, B_mem0, B_Wq, B_Wk, B_Wv, B_Wo, B_seg_len)
    return torch.concatenate([a, b], axis=-1)
```

```cpp
#include <cuda_runtime.h>
#include <cuda_bf16.h>
#include <cuda.h>
#include <stdint.h>

typedef __nv_bfloat16 bf16;

__device__ __forceinline__ uint32_t smem_u32(const void* p) { return (uint32_t)__cvta_generic_to_shared(p); }
__device__ __forceinline__ void mbar_init(uint32_t bar, uint32_t cnt) {
    asm volatile("mbarrier.init.shared::cta.b64 [%0], %1;" :: "r"(bar), "r"(cnt) : "memory");
}
__device__ __forceinline__ void mbar_expect_tx(uint32_t bar, uint32_t bytes) {
    asm volatile("mbarrier.arrive.expect_tx.shared::cta.b64 _, [%0], %1;" :: "r"(bar), "r"(bytes) : "memory");
}
__device__ __forceinline__ void mbar_arrive(uint32_t bar) {
    asm volatile("mbarrier.arrive.shared::cta.b64 _, [%0];" :: "r"(bar) : "memory");
}
__device__ __forceinline__ bool mbar_try_wait(uint32_t bar, uint32_t parity) {
    uint32_t ok;
    asm volatile("{\n.reg .pred p;\nmbarrier.try_wait.parity.shared::cta.b64 p, [%1], %2;\nselp.u32 %0, 1, 0, p;\n}"
                 : "=r"(ok) : "r"(bar), "r"(parity) : "memory");
    return ok != 0;
}
__device__ __forceinline__ void mbar_wait(uint32_t bar, uint32_t parity) {
    uint32_t n = 0;
    while (!mbar_try_wait(bar, parity)) { if (++n > (1u << 20)) break; }
}
__device__ __forceinline__ void fence_proxy_async_smem() { asm volatile("fence.proxy.async.shared::cta;" ::: "memory"); }
__device__ __forceinline__ void fence_proxy_async_all() { asm volatile("fence.proxy.async;" ::: "memory"); }
__device__ __forceinline__ void fence_mbar_init() { asm volatile("fence.mbarrier_init.release.cluster;" ::: "memory"); }

__device__ __forceinline__ void tma_load_3d(uint32_t dst, const CUtensorMap* tm, int c0, int c1, int c2, uint32_t bar) {
    asm volatile("cp.async.bulk.tensor.3d.shared::cluster.global.mbarrier::complete_tx::bytes [%0], [%1, {%3, %4, %5}], [%2];"
                 :: "r"(dst), "l"(tm), "r"(bar), "r"(c0), "r"(c1), "r"(c2) : "memory");
}
__device__ __forceinline__ void tma_load_2d(uint32_t dst, const CUtensorMap* tm, int c0, int c1, uint32_t bar) {
    asm volatile("cp.async.bulk.tensor.2d.shared::cluster.global.mbarrier::complete_tx::bytes [%0], [%1, {%3, %4}], [%2];"
                 :: "r"(dst), "l"(tm), "r"(bar), "r"(c0), "r"(c1) : "memory");
}
__device__ __forceinline__ void tma_store_3d(const CUtensorMap* tm, uint32_t src, int c0, int c1, int c2) {
    asm volatile("cp.async.bulk.tensor.3d.global.shared::cta.bulk_group [%0, {%2, %3, %4}], [%1];"
                 :: "l"(tm), "r"(src), "r"(c0), "r"(c1), "r"(c2) : "memory");
}
__device__ __forceinline__ void bulk_commit() { asm volatile("cp.async.bulk.commit_group;" ::: "memory"); }
__device__ __forceinline__ void bulk_wait_read0() { asm volatile("cp.async.bulk.wait_group.read 0;" ::: "memory"); }
__device__ __forceinline__ void bulk_wait_all0() { asm volatile("cp.async.bulk.wait_group 0;" ::: "memory"); }
__device__ __forceinline__ void prefetch_tmap(const CUtensorMap* tm) {
    asm volatile("prefetch.tensormap [%0];" :: "l"(tm) : "memory");
}

__device__ __forceinline__ void wg_fence() { asm volatile("wgmma.fence.sync.aligned;" ::: "memory"); }
__device__ __forceinline__ void wg_commit() { asm volatile("wgmma.commit_group.sync.aligned;" ::: "memory"); }
template <int N> __device__ __forceinline__ void wg_wait() { asm volatile("wgmma.wait_group.sync.aligned %0;" :: "n"(N) : "memory"); }

__device__ __forceinline__ void named_bar_sync(int id, int nthreads) {
    asm volatile("bar.sync %0, %1;" :: "r"(id), "r"(nthreads) : "memory");
}
__device__ __forceinline__ void named_bar_arrive(int id, int nthreads) {
    asm volatile("bar.arrive %0, %1;" :: "r"(id), "r"(nthreads) : "memory");
}

__device__ __forceinline__ uint64_t make_desc(uint32_t saddr, uint32_t lbo_bytes, uint32_t sbo_bytes) {
    return (uint64_t)((saddr & 0x3FFFF) >> 4) | ((uint64_t)(lbo_bytes >> 4) << 16) | ((uint64_t)(sbo_bytes >> 4) << 32) | ((uint64_t)1 << 62);
}

__device__ __forceinline__ uint32_t pack_bf16(float lo, float hi) {
    uint32_t r;
    asm("cvt.rn.bf16x2.f32 %0, %1, %2;" : "=r"(r) : "f"(hi), "f"(lo));
    return r;
}
__device__ __forceinline__ void stmatrix_x4(uint32_t addr, uint32_t r0, uint32_t r1, uint32_t r2, uint32_t r3) {
    asm volatile("stmatrix.sync.aligned.m8n8.x4.shared.b16 [%0], {%1,%2,%3,%4};" :: "r"(addr), "r"(r0), "r"(r1), "r"(r2), "r"(r3) : "memory");
}
__device__ __forceinline__ void ldmatrix_x4(uint32_t& r0, uint32_t& r1, uint32_t& r2, uint32_t& r3, uint32_t addr) {
    asm volatile("ldmatrix.sync.aligned.m8n8.x4.shared.b16 {%0,%1,%2,%3}, [%4];" : "=r"(r0), "=r"(r1), "=r"(r2), "=r"(r3) : "r"(addr) : "memory");
}
__device__ __forceinline__ void ldmatrix_x4_t(uint32_t& r0, uint32_t& r1, uint32_t& r2, uint32_t& r3, uint32_t addr) {
    asm volatile("ldmatrix.sync.aligned.m8n8.x4.trans.shared.b16 {%0,%1,%2,%3}, [%4];" : "=r"(r0), "=r"(r1), "=r"(r2), "=r"(r3) : "r"(addr) : "memory");
}
__device__ __forceinline__ void ldmatrix_x2(uint32_t& r0, uint32_t& r1, uint32_t addr) {
    asm volatile("ldmatrix.sync.aligned.m8n8.x2.shared.b16 {%0,%1}, [%2];" : "=r"(r0), "=r"(r1) : "r"(addr) : "memory");
}
__device__ __forceinline__ void ldmatrix_x2_t(uint32_t& r0, uint32_t& r1, uint32_t addr) {
    asm volatile("ldmatrix.sync.aligned.m8n8.x2.trans.shared.b16 {%0,%1}, [%2];" : "=r"(r0), "=r"(r1) : "r"(addr) : "memory");
}
__device__ __forceinline__ void mma16816(float* c, const uint32_t* a, uint32_t b0, uint32_t b1) {
    asm volatile("mma.sync.aligned.m16n8k16.row.col.f32.bf16.bf16.f32 {%0,%1,%2,%3}, {%4,%5,%6,%7}, {%8,%9}, {%0,%1,%2,%3};"
                 : "+f"(c[0]), "+f"(c[1]), "+f"(c[2]), "+f"(c[3]) : "r"(a[0]), "r"(a[1]), "r"(a[2]), "r"(a[3]), "r"(b0), "r"(b1));
}

__device__ __forceinline__ void wgmma_m64n128k16_ss_tb(float* d, uint64_t da, uint64_t db, int scale_d) {
    asm volatile(
        "{\n.reg .pred p;\nsetp.ne.b32 p, %66, 0;\n"
        "wgmma.mma_async.sync.aligned.m64n128k16.f32.bf16.bf16 "
        "{%0,%1,%2,%3,%4,%5,%6,%7,%8,%9,%10,%11,%12,%13,%14,%15,"
        "%16,%17,%18,%19,%20,%21,%22,%23,%24,%25,%26,%27,%28,%29,%30,%31,"
        "%32,%33,%34,%35,%36,%37,%38,%39,%40,%41,%42,%43,%44,%45,%46,%47,"
        "%48,%49,%50,%51,%52,%53,%54,%55,%56,%57,%58,%59,%60,%61,%62,%63},"
        " %64, %65, p, 1, 1, 0, 1;\n}\n"
        : "+f"(d[0]), "+f"(d[1]), "+f"(d[2]), "+f"(d[3]), "+f"(d[4]), "+f"(d[5]), "+f"(d[6]), "+f"(d[7]),
          "+f"(d[8]), "+f"(d[9]), "+f"(d[10]), "+f"(d[11]), "+f"(d[12]), "+f"(d[13]), "+f"(d[14]), "+f"(d[15]),
          "+f"(d[16]), "+f"(d[17]), "+f"(d[18]), "+f"(d[19]), "+f"(d[20]), "+f"(d[21]), "+f"(d[22]), "+f"(d[23]),
          "+f"(d[24]), "+f"(d[25]), "+f"(d[26]), "+f"(d[27]), "+f"(d[28]), "+f"(d[29]), "+f"(d[30]), "+f"(d[31]),
          "+f"(d[32]), "+f"(d[33]), "+f"(d[34]), "+f"(d[35]), "+f"(d[36]), "+f"(d[37]), "+f"(d[38]), "+f"(d[39]),
          "+f"(d[40]), "+f"(d[41]), "+f"(d[42]), "+f"(d[43]), "+f"(d[44]), "+f"(d[45]), "+f"(d[46]), "+f"(d[47]),
          "+f"(d[48]), "+f"(d[49]), "+f"(d[50]), "+f"(d[51]), "+f"(d[52]), "+f"(d[53]), "+f"(d[54]), "+f"(d[55]),
          "+f"(d[56]), "+f"(d[57]), "+f"(d[58]), "+f"(d[59]), "+f"(d[60]), "+f"(d[61]), "+f"(d[62]), "+f"(d[63])
        : "l"(da), "l"(db), "r"(scale_d));
}

__device__ __forceinline__ void wgmma_m64n128k16_rs(float* d, const uint32_t* a, uint64_t db, int scale_d) {
    asm volatile(
        "{\n.reg .pred p;\nsetp.ne.b32 p, %69, 0;\n"
        "wgmma.mma_async.sync.aligned.m64n128k16.f32.bf16.bf16 "
        "{%0,%1,%2,%3,%4,%5,%6,%7,%8,%9,%10,%11,%12,%13,%14,%15,"
        "%16,%17,%18,%19,%20,%21,%22,%23,%24,%25,%26,%27,%28,%29,%30,%31,"
        "%32,%33,%34,%35,%36,%37,%38,%39,%40,%41,%42,%43,%44,%45,%46,%47,"
        "%48,%49,%50,%51,%52,%53,%54,%55,%56,%57,%58,%59,%60,%61,%62,%63},"
        " {%64,%65,%66,%67}, %68, p, 1, 1, 0;\n}\n"
        : "+f"(d[0]), "+f"(d[1]), "+f"(d[2]), "+f"(d[3]), "+f"(d[4]), "+f"(d[5]), "+f"(d[6]), "+f"(d[7]),
          "+f"(d[8]), "+f"(d[9]), "+f"(d[10]), "+f"(d[11]), "+f"(d[12]), "+f"(d[13]), "+f"(d[14]), "+f"(d[15]),
          "+f"(d[16]), "+f"(d[17]), "+f"(d[18]), "+f"(d[19]), "+f"(d[20]), "+f"(d[21]), "+f"(d[22]), "+f"(d[23]),
          "+f"(d[24]), "+f"(d[25]), "+f"(d[26]), "+f"(d[27]), "+f"(d[28]), "+f"(d[29]), "+f"(d[30]), "+f"(d[31]),
          "+f"(d[32]), "+f"(d[33]), "+f"(d[34]), "+f"(d[35]), "+f"(d[36]), "+f"(d[37]), "+f"(d[38]), "+f"(d[39]),
          "+f"(d[40]), "+f"(d[41]), "+f"(d[42]), "+f"(d[43]), "+f"(d[44]), "+f"(d[45]), "+f"(d[46]), "+f"(d[47]),
          "+f"(d[48]), "+f"(d[49]), "+f"(d[50]), "+f"(d[51]), "+f"(d[52]), "+f"(d[53]), "+f"(d[54]), "+f"(d[55]),
          "+f"(d[56]), "+f"(d[57]), "+f"(d[58]), "+f"(d[59]), "+f"(d[60]), "+f"(d[61]), "+f"(d[62]), "+f"(d[63])
        : "r"(a[0]), "r"(a[1]), "r"(a[2]), "r"(a[3]), "l"(db), "r"(scale_d));
}
__device__ __forceinline__ void stmatrix_x4_t(uint32_t addr, uint32_t r0, uint32_t r1, uint32_t r2, uint32_t r3) {
    asm volatile("stmatrix.sync.aligned.m8n8.x4.trans.shared.b16 [%0], {%1,%2,%3,%4};" :: "r"(addr), "r"(r0), "r"(r1), "r"(r2), "r"(r3) : "memory");
}
template <int R> __device__ __forceinline__ void reg_alloc() { asm volatile("setmaxnreg.inc.sync.aligned.u32 %0;" :: "n"(R)); }
template <int R> __device__ __forceinline__ void reg_dealloc() { asm volatile("setmaxnreg.dec.sync.aligned.u32 %0;" :: "n"(R)); }

struct GemmWParams {
    CUtensorMap tmA;
    CUtensorMap tmB[3];
    CUtensorMap tmC;
    int ntiles_per_mat;
    int c_col64[3];
    int m_splits;
    int mtiles_per_cta;
    int flag_mats;
    unsigned int* flags;
};

constexpr int GW_NST = 11;
constexpr int GW_SMEM = GW_NST * 16384 + 32768 + 256;

__global__ void __launch_bounds__(384, 1) gemm_w_kernel(const __grid_constant__ GemmWParams p) {
    extern __shared__ __align__(1024) unsigned char smem[];
    const uint32_t sA = smem_u32(smem);
    const uint32_t sOut = sA + GW_NST * 16384;
    const uint32_t bars = sOut + 32768;
    const uint32_t barFull = bars, barEmpty = bars + 8 * GW_NST;
    const int warp = __shfl_sync(0xffffffff, threadIdx.x >> 5, 0), lane = threadIdx.x & 31;

    const int gnt = blockIdx.x / p.m_splits;
    const int ms = blockIdx.x % p.m_splits;
    const int mat = gnt / p.ntiles_per_mat;
    const int nt = gnt % p.ntiles_per_mat;
    const int tile0 = ms * p.mtiles_per_cta;
    const int ntl = p.mtiles_per_cta;

    if (threadIdx.x == 0) {
        for (int i = 0; i < GW_NST; i++) { mbar_init(barFull + 8 * i, 1); mbar_init(barEmpty + 8 * i, 8); }
        fence_mbar_init();
    }
    __syncthreads();

    const int wgi = __shfl_sync(0xffffffff, threadIdx.x >> 7, 0);
    asm volatile("griddepcontrol.launch_dependents;" ::: "memory");
    if (wgi == 0) {
        reg_dealloc<40>();
        if (warp == 0 && lane == 0) {
            const CUtensorMap* tmB = &p.tmB[mat];
            const int total = 8 + ntl * 8;
            for (int idx = 0; idx < total; idx++) {
                int slot = idx % GW_NST;
                if (idx >= GW_NST) mbar_wait(barEmpty + 8 * slot, ((idx / GW_NST) - 1) & 1);
                mbar_expect_tx(barFull + 8 * slot, 16384);
                if (idx < 8) tma_load_3d(sA + slot * 16384, tmB, 0, idx * 64, nt * 2, barFull + 8 * slot);
                else {
                    int t = (idx - 8) >> 3, j = (idx - 8) & 7;
                    tma_load_3d(sA + slot * 16384, &p.tmA, 0, (tile0 + t) * 128, j, barFull + 8 * slot);
                }
            }
        }
    } else {
        reg_alloc<232>();
        const int wg = (warp >> 2) - 1, wq = warp & 3;
        uint32_t w[32][4];
        float acc[64];
        {
            const int krow = (lane & 7) + ((lane >> 4) & 1) * 8;
            const int chunk = wq * 2 + ((lane >> 3) & 1);
#pragma unroll
            for (int kb = 0; kb < 8; kb++) {
                mbar_wait(barFull + 8 * kb, 0);
#pragma unroll
                for (int kk = 0; kk < 4; kk++) {
                    int r = kk * 16 + krow;
                    uint32_t addr = sA + kb * 16384 + wg * 8192 + r * 128 + ((chunk ^ (r & 7)) << 4);
                    ldmatrix_x4_t(w[kb * 4 + kk][0], w[kb * 4 + kk][1], w[kb * 4 + kk][2], w[kb * 4 + kk][3], addr);
                }
                __syncwarp();
                if (lane == 0) mbar_arrive(barEmpty + 8 * kb);
            }
        }
        const bool do_flag = (p.flags != nullptr) && (mat < p.flag_mats);
        const int tid_wg = threadIdx.x & 127;
        int pend_tile = -1;
        int idx = 8;
        for (int t = 0; t < ntl; t++) {
            int prev_slot = 0;
            if (wg == 0) { if (t > 0) named_bar_sync(3, 256); }
            else named_bar_sync(4, 256);
#pragma unroll
            for (int j = 0; j < 8; j++, idx++) {
                int slot = idx % GW_NST;
                mbar_wait(barFull + 8 * slot, (idx / GW_NST) & 1);
                wg_fence();
                uint64_t db = make_desc(sA + slot * 16384, 16, 1024);
#pragma unroll
                for (int kk = 0; kk < 4; kk++)
                    wgmma_m64n128k16_rs(acc, w[j * 4 + kk], db + (uint64_t)(kk * 2), (j | kk) != 0);
                wg_commit();
                if (j == 7) {
                    if (wg == 0) named_bar_arrive(4, 256);
                    else if (t + 1 < ntl) named_bar_arrive(3, 256);
                }
                if (j > 0) {
                    wg_wait<1>();
                    if (lane == 0) mbar_arrive(barEmpty + 8 * prev_slot);
                }
                prev_slot = slot;
            }
            wg_wait<0>();
            if (lane == 0) mbar_arrive(barEmpty + 8 * prev_slot);
            if (tid_wg == 0 && pend_tile >= 0) {
                if (do_flag) {
                    bulk_wait_all0();
                    fence_proxy_async_all();
                    __threadfence();
                    atomicAdd(p.flags + pend_tile, 1u);
                } else bulk_wait_read0();
            }
            named_bar_sync(1 + wg, 128);
            const uint32_t sbase = sOut + wg * 16384;
            const int mid = lane >> 3;
            const int chunk = wq * 2 + (mid & 1);
#pragma unroll
            for (int nb = 0; nb < 8; nb++) {
                const int a0 = nb * 8;
                uint32_t r0 = pack_bf16(acc[a0 + 0], acc[a0 + 1]);
                uint32_t r1 = pack_bf16(acc[a0 + 2], acc[a0 + 3]);
                uint32_t r2 = pack_bf16(acc[a0 + 4], acc[a0 + 5]);
                uint32_t r3 = pack_bf16(acc[a0 + 6], acc[a0 + 7]);
                int tok = nb * 16 + (mid >> 1) * 8 + (lane & 7);
                stmatrix_x4_t(sbase + tok * 128 + ((chunk ^ (tok & 7)) << 4), r0, r1, r2, r3);
            }
            fence_proxy_async_smem();
            named_bar_sync(1 + wg, 128);
            if (tid_wg == 0) {
                tma_store_3d(&p.tmC, sbase, 0, (tile0 + t) * 128, p.c_col64[mat] + nt * 2 + wg);
                bulk_commit();
            }
            pend_tile = tile0 + t;
        }
        if (pend_tile >= 0 && tid_wg == 0) {
            bulk_wait_all0();
            if (do_flag) {
                fence_proxy_async_all();
                __threadfence();
                atomicAdd(p.flags + pend_tile, 1u);
            }
        }
    }
}

struct ChainParams {
    CUtensorMap tmW[3];
    CUtensorMap tmWo;
    CUtensorMap tmKV;
    const bf16* mem0;
    bf16* kvmem;
    float* part;
    uint4* membuf;
    const unsigned int* flags;
    unsigned int flag_target;
    long long* dbg;
};

constexpr int CH_MEM_STRIDE = 1040;
constexpr int CH_Q_STRIDE = 144;
constexpr int CH_V_STRIDE = 272;
constexpr int CH_NKV = 4;
constexpr int CH_KV_BYTES = 12288;
constexpr int CH_OFF_WO = 0;
constexpr int CH_OFF_WV = 65536;
constexpr int CH_OFF_KV = 131072;
constexpr int CH_OFF_MEM = CH_OFF_KV + CH_NKV * CH_KV_BYTES;
constexpr int CH_OFF_Q = CH_OFF_MEM + 8320;
constexpr int CH_OFF_V = CH_OFF_Q + 2304;
constexpr int CH_OFF_O = CH_OFF_V + 2176;
constexpr int CH_OFF_RED1 = CH_OFF_O + 2176;
constexpr int CH_OFF_SC = CH_OFF_RED1 + 6144;
constexpr int CH_OFF_RED2 = CH_OFF_SC + 1280;
constexpr int CH_OFF_BAR = CH_OFF_RED2 + 2048;
constexpr int CH_SMEM = CH_OFF_BAR + 256;

__device__ __forceinline__ uint32_t mapa_u32(uint32_t addr, uint32_t rank) {
    uint32_t r; asm volatile("mapa.shared::cluster.u32 %0, %1, %2;" : "=r"(r) : "r"(addr), "r"(rank)); return r;
}
__device__ __forceinline__ void st_async_v4(uint32_t addr, uint32_t a, uint32_t b, uint32_t c, uint32_t d, uint32_t mbar) {
    asm volatile("st.async.shared::cluster.mbarrier::complete_tx::bytes.v4.b32 [%0], {%1,%2,%3,%4}, [%5];"
                 :: "r"(addr), "r"(a), "r"(b), "r"(c), "r"(d), "r"(mbar) : "memory");
}
__device__ __forceinline__ void st_async_v2(uint32_t addr, uint32_t a, uint32_t b, uint32_t mbar) {
    asm volatile("st.async.shared::cluster.mbarrier::complete_tx::bytes.v2.b32 [%0], {%1,%2}, [%3];"
                 :: "r"(addr), "r"(a), "r"(b), "r"(mbar) : "memory");
}
__device__ __forceinline__ bool mbar_try_wait_cl(uint32_t bar, uint32_t parity) {
    uint32_t ok;
    asm volatile("{\n.reg .pred p;\nmbarrier.try_wait.parity.acquire.cluster.shared::cta.b64 p, [%1], %2;\nselp.u32 %0, 1, 0, p;\n}"
                 : "=r"(ok) : "r"(bar), "r"(parity) : "memory");
    return ok != 0;
}
__device__ __forceinline__ void mbar_wait_cl(uint32_t bar, uint32_t parity) {
    uint32_t n = 0;
    while (!mbar_try_wait_cl(bar, parity)) { if (++n > (1u << 20)) break; }
}
__device__ __forceinline__ void cluster_sync_all() {
    asm volatile("barrier.cluster.arrive.aligned;\nbarrier.cluster.wait.aligned;" ::: "memory");
}
__device__ __forceinline__ uint4 ld_relaxed_v4(const void* p) {
    uint4 v;
    asm volatile("ld.relaxed.gpu.global.v4.u32 {%0,%1,%2,%3}, [%4];" : "=r"(v.x), "=r"(v.y), "=r"(v.z), "=r"(v.w) : "l"(p) : "memory");
    return v;
}
__device__ __forceinline__ void st_relaxed_v4(void* p, uint32_t a, uint32_t b, uint32_t c, uint32_t d) {
    asm volatile("st.relaxed.gpu.global.v4.u32 [%0], {%1,%2,%3,%4};" :: "l"(p), "r"(a), "r"(b), "r"(c), "r"(d) : "memory");
}
__device__ __forceinline__ unsigned int ld_acquire_u32(const unsigned int* p) {
    unsigned int v;
    asm volatile("ld.acquire.gpu.global.u32 %0, [%1];" : "=r"(v) : "l"(p) : "memory");
    return v;
}
__device__ __forceinline__ void lds128(uint32_t* r, uint32_t addr) {
    asm volatile("ld.shared.v4.u32 {%0,%1,%2,%3}, [%4];" : "=r"(r[0]), "=r"(r[1]), "=r"(r[2]), "=r"(r[3]) : "r"(addr) : "memory");
}
__device__ __forceinline__ float ex2_approx(float x) { float y; asm("ex2.approx.ftz.f32 %0, %1;" : "=f"(y) : "f"(x)); return y; }
__device__ __forceinline__ void mma_nv(float* c, const uint32_t* a, uint32_t b0, uint32_t b1) {
    asm("mma.sync.aligned.m16n8k16.row.col.f32.bf16.bf16.f32 {%0,%1,%2,%3}, {%4,%5,%6,%7}, {%8,%9}, {%0,%1,%2,%3};"
        : "+f"(c[0]), "+f"(c[1]), "+f"(c[2]), "+f"(c[3]) : "r"(a[0]), "r"(a[1]), "r"(a[2]), "r"(a[3]), "r"(b0), "r"(b1));
}

__global__ void __launch_bounds__(384, 1) chain_kernel(const __grid_constant__ ChainParams p) {
    extern __shared__ __align__(1024) unsigned char smem[];
    const uint32_t sb = smem_u32(smem);
    const int tid = threadIdx.x, lane = tid & 31;
    const int warp = __shfl_sync(0xffffffff, tid >> 5, 0);
    const int wgi = __shfl_sync(0xffffffff, tid >> 7, 0);
    const int head = blockIdx.x >> 1, half = blockIdx.x & 1;
    const uint32_t barSc = sb + CH_OFF_BAR, barV = barSc + 8, barLd = barSc + 16, barKV = barSc + 24, barKVE = barKV + 8 * CH_NKV;

    if (tid == 0) {
        mbar_init(barSc, 1); mbar_init(barV, 1); mbar_init(barLd, 1);
        for (int i = 0; i < CH_NKV; i++) { mbar_init(barKV + 8 * i, 1); mbar_init(barKVE + 8 * i, 4); }
        fence_mbar_init();
        mbar_expect_tx(barSc, 1280);
        mbar_expect_tx(barV, 1024);
    }
    __syncthreads();
    cluster_sync_all();
    const uint32_t sMem = sb + CH_OFF_MEM, sQ = sb + CH_OFF_Q, sK = sQ + 1152, sV = sb + CH_OFF_V, sO = sb + CH_OFF_O;
    const uint32_t sRed1 = sb + CH_OFF_RED1, sSc = sb + CH_OFF_SC, sRed2 = sb + CH_OFF_RED2;
    const uint32_t peer = half ^ 1;
    const int t4 = lane & 3, g8 = lane >> 2;
#define TS(i)

    if (wgi < 2) {
        reg_alloc<208>();
        const int g = warp >> 1, kh = warp & 1;
        const uint32_t rV = mapa_u32(sV, peer), rBarV = mapa_u32(barV, peer);
        uint32_t wqk[2][16][4];
        {
            const int c64 = head * 2 + half;
            const int krow = (lane & 7) + ((lane >> 4) & 1) * 8;
            const int chunk = g * 2 + ((lane >> 3) & 1);
            if (tid == 0) {
                mbar_expect_tx(barLd, 131072);
                tma_load_3d(sb + CH_OFF_WO, &p.tmW[0], 0, 0, c64, barLd);
                tma_load_3d(sb + CH_OFF_WO + 32768, &p.tmW[0], 0, 256, c64, barLd);
                tma_load_3d(sb + CH_OFF_WV, &p.tmW[1], 0, 0, c64, barLd);
                tma_load_3d(sb + CH_OFF_WV + 32768, &p.tmW[1], 0, 256, c64, barLd);
            }
            mbar_wait(barLd, 0);
#pragma unroll
            for (int m = 0; m < 2; m++)
#pragma unroll
                for (int ks = 0; ks < 16; ks++) {
                    int r = kh * 256 + ks * 16 + krow;
                    uint32_t addr = sb + (m == 0 ? CH_OFF_WO : CH_OFF_WV) + r * 128 + ((chunk ^ (r & 7)) << 4);
                    ldmatrix_x4_t(wqk[m][ks][0], wqk[m][ks][1], wqk[m][ks][2], wqk[m][ks][3], addr);
                }
            named_bar_sync(7, 256);
            if (tid == 0) {
                mbar_expect_tx(barLd, 131072);
                tma_load_3d(sb + CH_OFF_WV, &p.tmW[2], 0, 0, c64, barLd);
                tma_load_3d(sb + CH_OFF_WV + 32768, &p.tmW[2], 0, 256, c64, barLd);
                for (int i = 0; i < 4; i++) tma_load_3d(sb + CH_OFF_WO + i * 16384, &p.tmWo, 0, head * 128, half * 4 + i, barLd);
            }
            mbar_wait(barLd, 1);
            uint32_t f[16][4];
#pragma unroll
            for (int ks = 0; ks < 16; ks++) {
                int r = kh * 256 + ks * 16 + krow;
                ldmatrix_x4_t(f[ks][0], f[ks][1], f[ks][2], f[ks][3], sb + CH_OFF_WV + r * 128 + ((chunk ^ (r & 7)) << 4));
            }
            named_bar_sync(7, 256);
#pragma unroll
            for (int ks = 0; ks < 16; ks++)
                asm volatile("st.shared.v4.u32 [%0], {%1,%2,%3,%4};" :: "r"(sb + CH_OFF_WV + ((warp * 16 + ks) * 32 + lane) * 16), "r"(f[ks][0]), "r"(f[ks][1]), "r"(f[ks][2]), "r"(f[ks][3]) : "memory");
#pragma unroll
            for (int ks = 0; ks < 8; ks++)
#pragma unroll
                for (int mt = 0; mt < 2; mt++) {
                    int r = ks * 16 + krow;
                    int colchunk = warp * 4 + mt * 2 + ((lane >> 3) & 1);
                    ldmatrix_x4_t(f[ks * 2 + mt][0], f[ks * 2 + mt][1], f[ks * 2 + mt][2], f[ks * 2 + mt][3],
                                  sb + CH_OFF_WO + (colchunk >> 3) * 16384 + r * 128 + (((colchunk & 7) ^ (r & 7)) << 4));
                }
            named_bar_sync(7, 256);
#pragma unroll
            for (int i = 0; i < 16; i++)
                asm volatile("st.shared.v4.u32 [%0], {%1,%2,%3,%4};" :: "r"(sb + CH_OFF_WO + ((warp * 16 + i) * 32 + lane) * 16), "r"(f[i][0]), "r"(f[i][1]), "r"(f[i][2]), "r"(f[i][3]) : "memory");
            named_bar_sync(7, 256);
        }
        const uint32_t wvbase = sb + CH_OFF_WV + (warp * 16 * 32 + lane) * 16;
        const uint32_t wobase = sb + CH_OFF_WO + (warp * 16 * 32 + lane) * 16;
        const uint32_t bAddr = sMem + (lane & 7) * CH_MEM_STRIDE + (kh * 256 + (lane >> 3) * 8) * 2;

        for (int s = 0; s < 64; s++) {
            TS(0);
            uint32_t wv[16][4];
#pragma unroll
            for (int i = 0; i < 12; i++) lds128(wv[i], wvbase + i * 512);
            {
                const int tok0 = tid & 7, c = tid >> 3;
                uint4 v0, v1;
                if (s == 0) {
                    v0 = *reinterpret_cast<const uint4*>(p.mem0 + tok0 * 512 + c * 8);
                    v1 = *reinterpret_cast<const uint4*>(p.mem0 + tok0 * 512 + (c + 32) * 8);
                } else {
                    const uint4* src = p.membuf + (size_t)(s - 1) * 512 + tid;
                    uint32_t n = 0;
                    do { v0 = ld_relaxed_v4(src); v1 = ld_relaxed_v4(src + 256); } while ((v0.x == 0u || v1.x == 0u) && ++n < (1u << 22));
                }
                *reinterpret_cast<uint4*>(smem + CH_OFF_MEM + tok0 * CH_MEM_STRIDE + c * 16) = v0;
                *reinterpret_cast<uint4*>(smem + CH_OFF_MEM + tok0 * CH_MEM_STRIDE + (c + 32) * 16) = v1;
            }
            named_bar_sync(7, 256);
            TS(1);
            {
                float aq[2][4], ak[2][4];
#pragma unroll
                for (int i = 0; i < 4; i++) { aq[0][i] = aq[1][i] = ak[0][i] = ak[1][i] = 0.f; }
#pragma unroll
                for (int hb = 0; hb < 4; hb++) {
                    uint32_t b[2][4];
#pragma unroll
                    for (int kk = 0; kk < 2; kk++) ldmatrix_x4(b[kk][0], b[kk][1], b[kk][2], b[kk][3], bAddr + (hb * 2 + kk) * 64);
#pragma unroll
                    for (int kk = 0; kk < 2; kk++) {
                        const int k2 = (hb * 2 + kk) * 2;
                        mma_nv(aq[0], wqk[0][k2], b[kk][0], b[kk][1]);
                        mma_nv(ak[0], wqk[1][k2], b[kk][0], b[kk][1]);
                        mma_nv(aq[1], wqk[0][k2 + 1], b[kk][2], b[kk][3]);
                        mma_nv(ak[1], wqk[1][k2 + 1], b[kk][2], b[kk][3]);
                    }
                }
                float gv[4], kp[4];
#pragma unroll
                for (int i = 0; i < 4; i++) {
                    float q = aq[0][i] + aq[1][i], k = ak[0][i] + ak[1][i];
                    gv[i] = kh == 0 ? k : q;
                    kp[i] = kh == 0 ? q : k;
                }
                asm volatile("st.shared.v4.f32 [%0], {%1,%2,%3,%4};" :: "r"(sRed1 + warp * 512 + lane * 16), "f"(gv[0]), "f"(gv[1]), "f"(gv[2]), "f"(gv[3]) : "memory");
                named_bar_sync(1 + g, 64);
                float o0, o1, o2, o3;
                asm volatile("ld.shared.v4.f32 {%0,%1,%2,%3}, [%4];" : "=f"(o0), "=f"(o1), "=f"(o2), "=f"(o3) : "r"(sRed1 + (warp ^ 1) * 512 + lane * 16) : "memory");
                uint32_t r0 = pack_bf16(kp[0] + o0, kp[1] + o1);
                uint32_t r1 = pack_bf16(kp[2] + o2, kp[3] + o3);
                uint32_t dst = (kh == 0 ? sQ : sK) + (lane & 7) * CH_Q_STRIDE + (g * 16 + ((lane >> 3) & 1) * 8) * 2;
                asm volatile("stmatrix.sync.aligned.m8n8.x2.trans.shared.b16 [%0], {%1,%2};" :: "r"(dst), "r"(r0), "r"(r1) : "memory");
            }
            named_bar_arrive(5, 384);
            TS(2);
            {
                float av[2][4];
#pragma unroll
                for (int i = 0; i < 4; i++) { av[0][i] = av[1][i] = 0.f; }
#pragma unroll
                for (int i = 12; i < 16; i++) lds128(wv[i], wvbase + i * 512);
#pragma unroll
                for (int hb = 0; hb < 2; hb++) {
                    uint32_t b[4][4];
#pragma unroll
                    for (int kk = 0; kk < 4; kk++) ldmatrix_x4(b[kk][0], b[kk][1], b[kk][2], b[kk][3], bAddr + (hb * 4 + kk) * 64);
#pragma unroll
                    for (int kk = 0; kk < 4; kk++) {
                        mma_nv(av[0], wv[(hb * 4 + kk) * 2], b[kk][0], b[kk][1]);
                        mma_nv(av[1], wv[(hb * 4 + kk) * 2 + 1], b[kk][2], b[kk][3]);
                    }
                }
#pragma unroll
                for (int i = 0; i < 4; i++) av[0][i] += av[1][i];
                if (kh == 1) {
                    asm volatile("st.shared.v4.f32 [%0], {%1,%2,%3,%4};" :: "r"(sRed1 + 4096 + g * 512 + lane * 16), "f"(av[0][0]), "f"(av[0][1]), "f"(av[0][2]), "f"(av[0][3]) : "memory");
                }
                named_bar_sync(1 + g, 64);
                if (kh == 0) {
                    float o0, o1, o2, o3;
                    asm volatile("ld.shared.v4.f32 {%0,%1,%2,%3}, [%4];" : "=f"(o0), "=f"(o1), "=f"(o2), "=f"(o3) : "r"(sRed1 + 4096 + g * 512 + lane * 16) : "memory");
                    uint32_t r0 = pack_bf16(av[0][0] + o0, av[0][1] + o1);
                    uint32_t r1 = pack_bf16(av[0][2] + o2, av[0][3] + o3);
                    uint32_t off = (lane & 7) * CH_V_STRIDE + (half * 64 + g * 16 + ((lane >> 3) & 1) * 8) * 2;
                    asm volatile("stmatrix.sync.aligned.m8n8.x2.trans.shared.b16 [%0], {%1,%2};" :: "r"(sV + off), "r"(r0), "r"(r1) : "memory");
                    __syncwarp();
                    if (lane < 16) {
                        uint32_t f[4];
                        lds128(f, sV + off);
                        st_async_v4(rV + off, f[0], f[1], f[2], f[3], rBarV);
                    }
                }
            }
            named_bar_arrive(6, 384);
            TS(3);
            if (s == 63) break;
            uint32_t wo[16][4];
#pragma unroll
            for (int i = 0; i < 16; i++) lds128(wo[i], wobase + i * 512);
            named_bar_sync(8, 384);
            TS(4);
            const uint32_t tag = ((s >> 1) + 1) & 1;
            float* slot = p.part + (size_t)(s & 1) * (64 * 32 * 64);
            {
                float a2[2][2][4];
#pragma unroll
                for (int i = 0; i < 4; i++) { a2[0][0][i] = a2[0][1][i] = a2[1][0][i] = a2[1][1][i] = 0.f; }
                const uint32_t oAddr = sO + (lane & 7) * CH_V_STRIDE + ((lane >> 3) * 8) * 2;
                uint32_t b[4][4];
#pragma unroll
                for (int kk = 0; kk < 4; kk++) ldmatrix_x4(b[kk][0], b[kk][1], b[kk][2], b[kk][3], oAddr + kk * 64);
#pragma unroll
                for (int kk = 0; kk < 4; kk++) {
                    mma_nv(a2[0][0], wo[kk * 4 + 0], b[kk][0], b[kk][1]);
                    mma_nv(a2[1][0], wo[kk * 4 + 1], b[kk][0], b[kk][1]);
                    mma_nv(a2[0][1], wo[kk * 4 + 2], b[kk][2], b[kk][3]);
                    mma_nv(a2[1][1], wo[kk * 4 + 3], b[kk][2], b[kk][3]);
                }
#pragma unroll
                for (int mt = 0; mt < 2; mt++) {
                    float c0 = a2[mt][0][0] + a2[mt][1][0], c1 = a2[mt][0][1] + a2[mt][1][1];
                    float c2 = a2[mt][0][2] + a2[mt][1][2], c3 = a2[mt][0][3] + a2[mt][1][3];
                    float s0 = (lane & 1) ? c0 : c2, s1 = (lane & 1) ? c1 : c3;
                    float n0 = __shfl_xor_sync(0xffffffff, s0, 1), n1 = __shfl_xor_sync(0xffffffff, s1, 1);
                    float e0, e1, e2, e3;
                    if (lane & 1) { e0 = n0; e1 = n1; e2 = c2; e3 = c3; } else { e0 = c0; e1 = c1; e2 = n0; e3 = n1; }
                    int red = half * 32 + warp * 4 + mt * 2 + (lane & 1);
                    float* dst = slot + ((size_t)red * 32 + head) * 64 + g8 * 8 + (t4 >> 1) * 4;
                    st_relaxed_v4(dst, (__float_as_uint(e0) & ~1u) | tag, __float_as_uint(e1), __float_as_uint(e2), __float_as_uint(e3));
                }
            }
            TS(5);
            {
                const float* src = slot + (size_t)blockIdx.x * (32 * 64) + tid * 4;
                uint4 v0, v1;
                uint32_t n = 0;
                do { v0 = ld_relaxed_v4(src); v1 = ld_relaxed_v4(src + 1024); } while ((((v0.x ^ tag) | (v1.x ^ tag)) & 1u) && ++n < (1u << 22));
                TS(6);
                float f0 = __uint_as_float(v0.x) + __uint_as_float(v1.x), f1 = __uint_as_float(v0.y) + __uint_as_float(v1.y);
                float f2 = __uint_as_float(v0.z) + __uint_as_float(v1.z), f3 = __uint_as_float(v0.w) + __uint_as_float(v1.w);
                f0 += __shfl_xor_sync(0xffffffff, f0, 16); f1 += __shfl_xor_sync(0xffffffff, f1, 16);
                f2 += __shfl_xor_sync(0xffffffff, f2, 16); f3 += __shfl_xor_sync(0xffffffff, f3, 16);
                if (lane < 16) asm volatile("st.shared.v4.f32 [%0], {%1,%2,%3,%4};" :: "r"(sRed2 + warp * 256 + lane * 16), "f"(f0), "f"(f1), "f"(f2), "f"(f3) : "memory");
                named_bar_sync(7, 256);
                if (warp == 0) {
                    float u[8][2];
#pragma unroll
                    for (int w = 0; w < 8; w++) {
                        asm volatile("ld.shared.f32 %0, [%1];" : "=f"(u[w][0]) : "r"(sRed2 + w * 256 + ((2 * t4) * 8 + g8) * 4) : "memory");
                        asm volatile("ld.shared.f32 %0, [%1];" : "=f"(u[w][1]) : "r"(sRed2 + w * 256 + ((2 * t4 + 1) * 8 + g8) * 4) : "memory");
                    }
                    float a0 = ((u[0][0] + u[1][0]) + (u[2][0] + u[3][0])) + ((u[4][0] + u[5][0]) + (u[6][0] + u[7][0]));
                    float a1 = ((u[0][1] + u[1][1]) + (u[2][1] + u[3][1])) + ((u[4][1] + u[5][1]) + (u[6][1] + u[7][1]));
                    uint32_t m = pack_bf16(a0, a1);
                    uint32_t m1 = __shfl_down_sync(0xffffffff, m, 1), m2 = __shfl_down_sync(0xffffffff, m, 2), m3 = __shfl_down_sync(0xffffffff, m, 3);
                    if (t4 == 0) {
                        if (m == 0u) m = 0x8000u;
                        st_relaxed_v4(p.membuf + (size_t)s * 512 + blockIdx.x * 8 + g8, m, m1, m2, m3);
                    }
                }
                TS(7);
            }
        }
    } else {
        reg_dealloc<88>();
        const int aw = warp - 8;
        const uint32_t rSc = mapa_u32(sSc, peer), rBarSc = mapa_u32(barSc, peer);
        const float sm_scale = 0.08838834764831845f * 1.4426950408889634f;
        const int kc64 = 64 + head * 2 + half, vc64 = 128 + head * 2;
        auto issue_kv = [&](int s) {
            if ((s & 3) == 0) {
                uint32_t n = 0;
                while (ld_acquire_u32(p.flags + (s >> 2)) < p.flag_target) { if (++n > (1u << 22)) break; }
                fence_proxy_async_all();
            }
            int st = s % CH_NKV;
            uint32_t base = sb + CH_OFF_KV + st * CH_KV_BYTES;
            mbar_expect_tx(barKV + 8 * st, CH_KV_BYTES);
            tma_load_3d(base, &p.tmKV, 0, s * 32, kc64, barKV + 8 * st);
            tma_load_3d(base + 4096, &p.tmKV, 0, s * 32, vc64, barKV + 8 * st);
            tma_load_3d(base + 8192, &p.tmKV, 0, s * 32, vc64 + 1, barKV + 8 * st);
        };
        if (aw == 3 && lane == 0) { for (int s = 0; s < CH_NKV - 1; s++) issue_kv(s); }
        for (int s = 0; s < 64; s++) {
            const uint32_t par = s & 1;
            const int st = s % CH_NKV;
            const uint32_t sKx = sb + CH_OFF_KV + st * CH_KV_BYTES, sVx = sKx + 4096;
            mbar_wait(barKV + 8 * st, (s / CH_NKV) & 1);
            uint32_t kb[2][4][4];
#pragma unroll
            for (int kp = 0; kp < 2; kp++)
#pragma unroll
                for (int n = 0; n < 4; n++) {
                    int row = n * 8 + (lane & 7);
                    ldmatrix_x4(kb[kp][n][0], kb[kp][n][1], kb[kp][n][2], kb[kp][n][3], sKx + row * 128 + (((kp * 4 + (lane >> 3)) ^ (row & 7)) << 4));
                }
            named_bar_sync(5, 384);
            TS(0);
            float sc[5][4];
#pragma unroll
            for (int n = 0; n < 5; n++) { sc[n][0] = sc[n][1] = sc[n][2] = sc[n][3] = 0.f; }
            {
                uint32_t a[4][4];
                ldmatrix_x4(a[0][0], a[0][2], a[1][0], a[1][2], sQ + (lane & 7) * CH_Q_STRIDE + ((lane >> 3) * 8) * 2);
                ldmatrix_x4(a[2][0], a[2][2], a[3][0], a[3][2], sQ + (lane & 7) * CH_Q_STRIDE + (32 + (lane >> 3) * 8) * 2);
#pragma unroll
                for (int i = 0; i < 4; i++) { a[i][1] = 0u; a[i][3] = 0u; }
                uint32_t km[2][4];
                ldmatrix_x4(km[0][0], km[0][1], km[0][2], km[0][3], sK + (lane & 7) * CH_Q_STRIDE + ((lane >> 3) * 8) * 2);
                ldmatrix_x4(km[1][0], km[1][1], km[1][2], km[1][3], sK + (lane & 7) * CH_Q_STRIDE + (32 + (lane >> 3) * 8) * 2);
#pragma unroll
                for (int kp = 0; kp < 2; kp++) {
#pragma unroll
                    for (int n = 0; n < 4; n++) mma_nv(sc[n + 1], a[kp * 2], kb[kp][n][0], kb[kp][n][1]);
                    mma_nv(sc[0], a[kp * 2], km[kp][0], km[kp][1]);
#pragma unroll
                    for (int n = 0; n < 4; n++) mma_nv(sc[n + 1], a[kp * 2 + 1], kb[kp][n][2], kb[kp][n][3]);
                    mma_nv(sc[0], a[kp * 2 + 1], km[kp][2], km[kp][3]);
                }
            }
            if (aw == 0) {
#pragma unroll
                for (int n = 0; n < 5; n++) st_async_v2(rSc + n * 256 + lane * 8, __float_as_uint(sc[n][0]), __float_as_uint(sc[n][1]), rBarSc);
            }
            TS(1);
            mbar_wait(barSc, par);
            TS(2);
            if (tid == 256) mbar_expect_tx(barSc, 1280);
            float mx = -3.0e38f;
#pragma unroll
            for (int n = 0; n < 5; n++) {
                float p0, p1;
                asm volatile("ld.shared.v2.f32 {%0,%1}, [%2];" : "=f"(p0), "=f"(p1) : "r"(sSc + n * 256 + lane * 8) : "memory");
                sc[n][0] += p0; sc[n][1] += p1;
                mx = fmaxf(mx, fmaxf(sc[n][0], sc[n][1]));
            }
            mx = fmaxf(mx, __shfl_xor_sync(0xffffffff, mx, 1));
            mx = fmaxf(mx, __shfl_xor_sync(0xffffffff, mx, 2));
            float sum = 0.f;
            const float mb = mx * sm_scale;
#pragma unroll
            for (int n = 0; n < 5; n++) {
                sc[n][0] = ex2_approx(sc[n][0] * sm_scale - mb);
                sc[n][1] = ex2_approx(sc[n][1] * sm_scale - mb);
                sum += sc[n][0] + sc[n][1];
            }
            sum += __shfl_xor_sync(0xffffffff, sum, 1);
            sum += __shfl_xor_sync(0xffffffff, sum, 2);
            const float inv = __fdividef(1.0f, sum);
            uint32_t pa[3][4];
            pa[0][0] = pack_bf16(sc[0][0] * inv, sc[0][1] * inv); pa[0][2] = pack_bf16(sc[1][0] * inv, sc[1][1] * inv);
            pa[1][0] = pack_bf16(sc[2][0] * inv, sc[2][1] * inv); pa[1][2] = pack_bf16(sc[3][0] * inv, sc[3][1] * inv);
            pa[2][0] = pack_bf16(sc[4][0] * inv, sc[4][1] * inv); pa[2][2] = 0u;
            pa[0][1] = pa[0][3] = pa[1][1] = pa[1][3] = pa[2][1] = pa[2][3] = 0u;
            TS(3);
            named_bar_sync(6, 384);
            mbar_wait(barV, par);
            TS(4);
            if (tid == 256) mbar_expect_tx(barV, 1024);
            float oc[4][4];
#pragma unroll
            for (int i = 0; i < 4; i++) { oc[0][i] = oc[1][i] = oc[2][i] = oc[3][i] = 0.f; }
            const int kr = (lane & 7), khi = (lane >> 3) & 1, dch = (lane >> 4) & 1;
            {
                uint32_t b[3][2][4];
#pragma unroll
                for (int ks = 0; ks < 3; ks++)
#pragma unroll
                    for (int dp = 0; dp < 2; dp++) {
                        int key = ks * 16 + khi * 8 + kr;
                        int dchunk = aw * 4 + dp * 2 + dch;
                        uint32_t addr;
                        if (key < 8 || key >= 40) addr = sV + kr * CH_V_STRIDE + dchunk * 16;
                        else { int row = key - 8; addr = sVx + (dchunk >> 3) * 4096 + row * 128 + (((dchunk & 7) ^ (row & 7)) << 4); }
                        ldmatrix_x4_t(b[ks][dp][0], b[ks][dp][1], b[ks][dp][2], b[ks][dp][3], addr);
                    }
#pragma unroll
                for (int ks = 0; ks < 3; ks++)
#pragma unroll
                    for (int dp = 0; dp < 2; dp++) {
                        mma_nv(oc[dp * 2], pa[ks], b[ks][dp][0], b[ks][dp][1]);
                        mma_nv(oc[dp * 2 + 1], pa[ks], b[ks][dp][2], b[ks][dp][3]);
                    }
            }
#pragma unroll
            for (int n = 0; n < 4; n++) {
                uint32_t r = pack_bf16(oc[n][0], oc[n][1]);
                asm volatile("st.shared.u32 [%0], %1;" :: "r"(sO + g8 * CH_V_STRIDE + (aw * 32 + n * 8 + t4 * 2) * 2), "r"(r) : "memory");
            }
            if (s < 63) named_bar_arrive(8, 384);
            TS(5);
            {
                int i = tid - 256;
                int which = i >> 6, tok = (i >> 3) & 7, c = i & 7;
                uint4 v = which == 0 ? *reinterpret_cast<const uint4*>(smem + CH_OFF_Q + 1152 + tok * CH_Q_STRIDE + c * 16)
                                     : *reinterpret_cast<const uint4*>(smem + CH_OFF_V + tok * CH_V_STRIDE + half * 128 + c * 16);
                *reinterpret_cast<uint4*>(p.kvmem + ((size_t)s * 8 + tok) * 8192 + which * 4096 + head * 128 + half * 64 + c * 8) = v;
            }
            if (aw == 3 && lane == 0 && s + CH_NKV - 1 < 64) issue_kv(s + CH_NKV - 1);
        }
    }
    __syncthreads();
    cluster_sync_all();
}

struct AttnAParams {
    CUtensorMap tmKV;
    const bf16* qkv;
    bf16* o;
};
constexpr int AA_KT = 256;
constexpr int AA_NST = 3;
constexpr int AA_SMEM = AA_NST * 2 * AA_KT * 32 + 64;

__device__ __forceinline__ float ex2a(float x) { float y; asm("ex2.approx.ftz.f32 %0, %1;" : "=f"(y) : "f"(x)); return y; }
__device__ __forceinline__ void mma_f(float* c, const uint32_t* a, uint32_t b0, uint32_t b1) {
    asm("mma.sync.aligned.m16n8k16.row.col.f32.bf16.bf16.f32 {%0,%1,%2,%3}, {%4,%5,%6,%7}, {%8,%9}, {%0,%1,%2,%3};"
        : "+f"(c[0]), "+f"(c[1]), "+f"(c[2]), "+f"(c[3]) : "r"(a[0]), "r"(a[1]), "r"(a[2]), "r"(a[3]), "r"(b0), "r"(b1));
}

__global__ void __launch_bounds__(256, 2) attn_a_kernel(const __grid_constant__ AttnAParams p) {
    extern __shared__ __align__(1024) unsigned char smem[];
    const uint32_t sb = smem_u32(smem);
    const uint32_t bars = sb + AA_NST * 2 * AA_KT * 32;
    const int tid = threadIdx.x, lane = tid & 31, warp = tid >> 5;
    const int head = blockIdx.x >> 3, qt = blockIdx.x & 7;
    const int t4 = lane & 3, g8 = lane >> 2;
    constexpr int NT = 2048 / AA_KT;

    if (tid == 0) {
        for (int i = 0; i < AA_NST; i++) { mbar_init(bars + 8 * i, 1); mbar_init(bars + 8 * (AA_NST + i), 8); }
        fence_mbar_init();
    }
    __syncthreads();
    auto issue = [&](int t) {
        int st = t % AA_NST;
        uint32_t dst = sb + st * (2 * AA_KT * 32);
        mbar_expect_tx(bars + 8 * st, 2 * AA_KT * 32);
        tma_load_2d(dst, &p.tmKV, 512 + head * 16, t * AA_KT, bars + 8 * st);
        tma_load_2d(dst + AA_KT * 32, &p.tmKV, 1024 + head * 16, t * AA_KT, bars + 8 * st);
    };
    if (tid == 0) { for (int t = 0; t < AA_NST; t++) issue(t); }

    uint32_t qa[2][4];
    const int row0 = qt * 256 + warp * 32;
#pragma unroll
    for (int m = 0; m < 2; m++) {
        const bf16* q = p.qkv + (size_t)(row0 + m * 16 + g8) * 1536 + head * 16 + t4 * 2;
        qa[m][0] = *reinterpret_cast<const uint32_t*>(q);
        qa[m][1] = *reinterpret_cast<const uint32_t*>(q + 8 * 1536);
        qa[m][2] = *reinterpret_cast<const uint32_t*>(q + 8);
        qa[m][3] = *reinterpret_cast<const uint32_t*>(q + 8 * 1536 + 8);
    }
    const float sc = 0.25f * 1.4426950408889634f;
    float mrow[2][2], oacc[2][2][4], lacc[2][4];
#pragma unroll
    for (int m = 0; m < 2; m++) {
        mrow[m][0] = mrow[m][1] = -3.0e38f;
#pragma unroll
        for (int i = 0; i < 4; i++) { oacc[m][0][i] = oacc[m][1][i] = 0.f; lacc[m][i] = 0.f; }
    }
    const uint32_t ones = 0x3F803F80u;
    const int lr = lane & 7, lm = lane >> 3;
    const int krow = (lm >> 1) * 8 + lr, kch = lm & 1;
    const uint32_t koff = krow * 32 + ((kch ^ ((krow >> 2) & 1)) << 4);
    const int vrow = (lm & 1) * 8 + lr, vch = lm >> 1;
    const uint32_t voff = vrow * 32 + ((vch ^ ((vrow >> 2) & 1)) << 4);

    for (int t = 0; t < NT; t++) {
        const int st = t % AA_NST;
        mbar_wait(bars + 8 * st, (t / AA_NST) & 1);
        const uint32_t sK = sb + st * (2 * AA_KT * 32), sV = sK + AA_KT * 32;
#pragma unroll 1
        for (int kb = 0; kb < AA_KT / 64; kb++) {
            float s[2][8][4];
#pragma unroll
            for (int np = 0; np < 4; np++) {
                uint32_t b0, b1, b2, b3;
                ldmatrix_x4(b0, b1, b2, b3, sK + (kb * 64 + np * 16) * 32 + koff);
#pragma unroll
                for (int m = 0; m < 2; m++) {
#pragma unroll
                    for (int i = 0; i < 4; i++) { s[m][np * 2][i] = 0.f; s[m][np * 2 + 1][i] = 0.f; }
                    mma_f(s[m][np * 2], qa[m], b0, b1);
                    mma_f(s[m][np * 2 + 1], qa[m], b2, b3);
                }
            }
            uint32_t pa[2][4][4];
#pragma unroll
            for (int m = 0; m < 2; m++) {
                float mx0 = s[m][0][0], mx1 = s[m][0][2];
#pragma unroll
                for (int n = 0; n < 8; n++) {
                    mx0 = fmaxf(mx0, fmaxf(s[m][n][0], s[m][n][1]));
                    mx1 = fmaxf(mx1, fmaxf(s[m][n][2], s[m][n][3]));
                }
                mx0 = fmaxf(mx0, __shfl_xor_sync(0xffffffff, mx0, 1)); mx0 = fmaxf(mx0, __shfl_xor_sync(0xffffffff, mx0, 2));
                mx1 = fmaxf(mx1, __shfl_xor_sync(0xffffffff, mx1, 1)); mx1 = fmaxf(mx1, __shfl_xor_sync(0xffffffff, mx1, 2));
                const float mn0 = fmaxf(mrow[m][0], mx0), mn1 = fmaxf(mrow[m][1], mx1);
                const float a0 = ex2a((mrow[m][0] - mn0) * sc), a1 = ex2a((mrow[m][1] - mn1) * sc);
                mrow[m][0] = mn0; mrow[m][1] = mn1;
                const float mb0 = mn0 * sc, mb1 = mn1 * sc;
#pragma unroll
                for (int d = 0; d < 2; d++) { oacc[m][d][0] *= a0; oacc[m][d][1] *= a0; oacc[m][d][2] *= a1; oacc[m][d][3] *= a1; }
                lacc[m][0] *= a0; lacc[m][2] *= a1;
#pragma unroll
                for (int n = 0; n < 8; n++) {
                    float p0 = ex2a(fmaf(s[m][n][0], sc, -mb0)), p1 = ex2a(fmaf(s[m][n][1], sc, -mb0));
                    float p2 = ex2a(fmaf(s[m][n][2], sc, -mb1)), p3 = ex2a(fmaf(s[m][n][3], sc, -mb1));
                    pa[m][n >> 1][(n & 1) * 2 + 0] = pack_bf16(p0, p1);
                    pa[m][n >> 1][(n & 1) * 2 + 1] = pack_bf16(p2, p3);
                }
            }
#pragma unroll
            for (int ks = 0; ks < 4; ks++) {
                uint32_t b0, b1, b2, b3;
                ldmatrix_x4_t(b0, b1, b2, b3, sV + (kb * 64 + ks * 16) * 32 + voff);
#pragma unroll
                for (int m = 0; m < 2; m++) {
                    mma_f(oacc[m][0], pa[m][ks], b0, b1);
                    mma_f(oacc[m][1], pa[m][ks], b2, b3);
                    mma_f(lacc[m], pa[m][ks], ones, ones);
                }
            }
        }
        __syncwarp();
        if (lane == 0) mbar_arrive(bars + 8 * (AA_NST + st));
        if (tid == 0 && t + AA_NST < NT) {
            mbar_wait(bars + 8 * (AA_NST + st), (t / AA_NST) & 1);
            issue(t + AA_NST);
        }
    }
#pragma unroll
    for (int m = 0; m < 2; m++) {
        const float i0 = 1.0f / lacc[m][0], i1 = 1.0f / lacc[m][2];
        bf16* o = p.o + (size_t)(row0 + m * 16 + g8) * 512 + head * 16 + t4 * 2;
#pragma unroll
        for (int d = 0; d < 2; d++) {
            *reinterpret_cast<uint32_t*>(o + d * 8) = pack_bf16(oacc[m][d][0] * i0, oacc[m][d][1] * i0);
            *reinterpret_cast<uint32_t*>(o + 8 * 512 + d * 8) = pack_bf16(oacc[m][d][2] * i1, oacc[m][d][3] * i1);
        }
    }
}

struct AttnBParams {
    CUtensorMap tmQKV;
    CUtensorMap tmKVM;
    CUtensorMap tmO;
    const unsigned int* seg_flags;
    unsigned int seg_target;
};
constexpr int AB_WARP_BYTES = 28672;
constexpr int AB_SMEM = 4 * AB_WARP_BYTES + 64;

__global__ void __launch_bounds__(128, 2) attn_b_kernel(const __grid_constant__ AttnBParams p) {
    extern __shared__ __align__(1024) unsigned char smem[];
    const int tid = threadIdx.x, lane = tid & 31, warp = tid >> 5;
    const uint32_t sb = smem_u32(smem) + warp * AB_WARP_BYTES;
    const uint32_t bar = smem_u32(smem) + 4 * AB_WARP_BYTES + warp * 8;
    const int seg = blockIdx.x >> 3, head = (blockIdx.x & 7) * 4 + warp;
    const int t4 = lane & 3, g8 = lane >> 2;
    const uint32_t sQ = sb, sK = sb + 8192, sV = sb + 16384, sKm = sb + 24576, sVm = sb + 26624;
    if (lane == 0) {
        mbar_init(bar, 1);
        fence_mbar_init();
        if (p.seg_flags) {
            uint32_t n = 0;
            while (ld_acquire_u32(p.seg_flags + seg) < p.seg_target) { if (++n > (1u << 24)) break; __nanosleep(200); }
            fence_proxy_async_all();
        }
        mbar_expect_tx(bar, AB_WARP_BYTES);
#pragma unroll
        for (int h = 0; h < 2; h++) {
            tma_load_3d(sQ + h * 4096, &p.tmQKV, 0, seg * 32, head * 2 + h, bar);
            tma_load_3d(sK + h * 4096, &p.tmQKV, 0, seg * 32, 64 + head * 2 + h, bar);
            tma_load_3d(sV + h * 4096, &p.tmQKV, 0, seg * 32, 128 + head * 2 + h, bar);
            tma_load_3d(sKm + h * 1024, &p.tmKVM, 0, seg * 8, head * 2 + h, bar);
            tma_load_3d(sVm + h * 1024, &p.tmKVM, 0, seg * 8, 64 + head * 2 + h, bar);
        }
    }
    __syncwarp();
    mbar_wait(bar, 0);
    const int lr = lane & 7, lm = lane >> 3;
    float s[2][5][4];
#pragma unroll
    for (int m = 0; m < 2; m++)
#pragma unroll
        for (int n = 0; n < 5; n++)
#pragma unroll
            for (int i = 0; i < 4; i++) s[m][n][i] = 0.f;
#pragma unroll
    for (int kp = 0; kp < 4; kp++) {
        const int hb = kp >> 1, c0 = (kp & 1) * 4;
        uint32_t a[2][2][4];
#pragma unroll
        for (int m = 0; m < 2; m++)
#pragma unroll
            for (int ks = 0; ks < 2; ks++) {
                int row = m * 16 + (lm & 1) * 8 + lr, ch = c0 + ks * 2 + (lm >> 1);
                ldmatrix_x4(a[m][ks][0], a[m][ks][1], a[m][ks][2], a[m][ks][3], sQ + hb * 4096 + row * 128 + ((ch ^ (row & 7)) << 4));
            }
#pragma unroll
        for (int n = 0; n < 5; n++) {
            uint32_t b0, b1, b2, b3;
            int ch = c0 + lm;
            if (n == 0) ldmatrix_x4(b0, b1, b2, b3, sKm + hb * 1024 + lr * 128 + ((ch ^ lr) << 4));
            else { int row = (n - 1) * 8 + lr; ldmatrix_x4(b0, b1, b2, b3, sK + hb * 4096 + row * 128 + ((ch ^ (row & 7)) << 4)); }
#pragma unroll
            for (int m = 0; m < 2; m++) { mma_f(s[m][n], a[m][0], b0, b1); mma_f(s[m][n], a[m][1], b2, b3); }
        }
    }
    const float sc = 0.08838834764831845f * 1.4426950408889634f;
    uint32_t pa[2][3][4];
    float inv[2][2];
#pragma unroll
    for (int m = 0; m < 2; m++) {
        const int r0 = m * 16 + g8, r1 = r0 + 8;
        float mx0 = -3.0e38f, mx1 = -3.0e38f;
#pragma unroll
        for (int n = 0; n < 5; n++) {
            if (n > 0) {
                int j = (n - 1) * 8 + t4 * 2;
                if (j > r0) s[m][n][0] = -3.0e38f;
                if (j + 1 > r0) s[m][n][1] = -3.0e38f;
                if (j > r1) s[m][n][2] = -3.0e38f;
                if (j + 1 > r1) s[m][n][3] = -3.0e38f;
            }
            mx0 = fmaxf(mx0, fmaxf(s[m][n][0], s[m][n][1]));
            mx1 = fmaxf(mx1, fmaxf(s[m][n][2], s[m][n][3]));
        }
        mx0 = fmaxf(mx0, __shfl_xor_sync(0xffffffff, mx0, 1)); mx0 = fmaxf(mx0, __shfl_xor_sync(0xffffffff, mx0, 2));
        mx1 = fmaxf(mx1, __shfl_xor_sync(0xffffffff, mx1, 1)); mx1 = fmaxf(mx1, __shfl_xor_sync(0xffffffff, mx1, 2));
        const float mb0 = mx0 * sc, mb1 = mx1 * sc;
        float l0 = 0.f, l1 = 0.f;
#pragma unroll
        for (int n = 0; n < 5; n++) {
            s[m][n][0] = ex2a(fmaf(s[m][n][0], sc, -mb0)); s[m][n][1] = ex2a(fmaf(s[m][n][1], sc, -mb0));
            s[m][n][2] = ex2a(fmaf(s[m][n][2], sc, -mb1)); s[m][n][3] = ex2a(fmaf(s[m][n][3], sc, -mb1));
            l0 += s[m][n][0] + s[m][n][1]; l1 += s[m][n][2] + s[m][n][3];
        }
        l0 += __shfl_xor_sync(0xffffffff, l0, 1); l0 += __shfl_xor_sync(0xffffffff, l0, 2);
        l1 += __shfl_xor_sync(0xffffffff, l1, 1); l1 += __shfl_xor_sync(0xffffffff, l1, 2);
        inv[m][0] = 1.0f / l0; inv[m][1] = 1.0f / l1;
#pragma unroll
        for (int n = 0; n < 5; n++) {
            pa[m][n >> 1][(n & 1) * 2 + 0] = pack_bf16(s[m][n][0] * inv[m][0], s[m][n][1] * inv[m][0]);
            pa[m][n >> 1][(n & 1) * 2 + 1] = pack_bf16(s[m][n][2] * inv[m][1], s[m][n][3] * inv[m][1]);
        }
        pa[m][2][2] = 0u; pa[m][2][3] = 0u;
    }
    __syncwarp();
#pragma unroll
    for (int dq = 0; dq < 4; dq++) {
        float oc[2][4][4];
#pragma unroll
        for (int m = 0; m < 2; m++)
#pragma unroll
            for (int n = 0; n < 4; n++)
#pragma unroll
                for (int i = 0; i < 4; i++) oc[m][n][i] = 0.f;
        const int hb = dq >> 1, c0 = (dq & 1) * 4;
#pragma unroll
        for (int ks = 0; ks < 3; ks++) {
#pragma unroll
            for (int dp = 0; dp < 2; dp++) {
                int key = ks * 16 + (lm & 1) * 8 + lr, ch = c0 + dp * 2 + (lm >> 1);
                uint32_t addr;
                if (key < 8 || key >= 40) addr = sVm + hb * 1024 + lr * 128 + ((ch ^ lr) << 4);
                else { int row = key - 8; addr = sV + hb * 4096 + row * 128 + ((ch ^ (row & 7)) << 4); }
                uint32_t b0, b1, b2, b3;
                ldmatrix_x4_t(b0, b1, b2, b3, addr);
#pragma unroll
                for (int m = 0; m < 2; m++) { mma_f(oc[m][dp * 2], pa[m][ks], b0, b1); mma_f(oc[m][dp * 2 + 1], pa[m][ks], b2, b3); }
            }
        }
#pragma unroll
        for (int m = 0; m < 2; m++)
#pragma unroll
            for (int dp = 0; dp < 2; dp++) {
                int row = m * 16 + (lm & 1) * 8 + lr, ch = c0 + dp * 2 + (lm >> 1);
                stmatrix_x4(sQ + hb * 4096 + row * 128 + ((ch ^ (row & 7)) << 4),
                            pack_bf16(oc[m][dp * 2][0], oc[m][dp * 2][1]), pack_bf16(oc[m][dp * 2][2], oc[m][dp * 2][3]),
                            pack_bf16(oc[m][dp * 2 + 1][0], oc[m][dp * 2 + 1][1]), pack_bf16(oc[m][dp * 2 + 1][2], oc[m][dp * 2 + 1][3]));
            }
    }
    fence_proxy_async_smem();
    __syncwarp();
    if (lane == 0) {
        tma_store_3d(&p.tmO, sQ, 0, seg * 32, head * 2);
        tma_store_3d(&p.tmO, sQ + 4096, 0, seg * 32, head * 2 + 1);
        bulk_commit();
        bulk_wait_read0();
    }
}

struct GemmSParams {
    CUtensorMap tmA;
    CUtensorMap tmB;
    CUtensorMap tmC;
    int n_tiles;
    int kblocks_half;
    int c_col64;
};
constexpr int GS_NST = 5;
constexpr int GS_SMEM = GS_NST * 32768 + 32768 + 256;

__global__ void __launch_bounds__(288, 1) gemm_s_kernel(const __grid_constant__ GemmSParams p) {
    extern __shared__ __align__(1024) unsigned char smem[];
    const uint32_t sS = smem_u32(smem);
    const uint32_t sR = sS + GS_NST * 32768;
    const uint32_t bars = sR + 32768;
    const uint32_t barFull = bars, barEmpty = bars + 8 * GS_NST, barRed = bars + 16 * GS_NST;
    const int warp = __shfl_sync(0xffffffff, threadIdx.x >> 5, 0), lane = threadIdx.x & 31;
    const int tile = blockIdx.x >> 1, kh = blockIdx.x & 1;
    const int mt = tile / p.n_tiles, nt = tile % p.n_tiles;
    if (threadIdx.x == 0) {
        for (int i = 0; i < GS_NST; i++) { mbar_init(barFull + 8 * i, 1); mbar_init(barEmpty + 8 * i, 8); }
        mbar_init(barRed, 1);
        fence_mbar_init();
        mbar_expect_tx(barRed, 32768);
    }
    __syncthreads();
    cluster_sync_all();
    if (warp == 8) {
        if (lane == 0) {
            for (int i = 0; i < p.kblocks_half; i++) {
                int slot = i % GS_NST;
                if (i >= GS_NST) mbar_wait(barEmpty + 8 * slot, ((i / GS_NST) - 1) & 1);
                mbar_expect_tx(barFull + 8 * slot, 32768);
                int kb = kh * p.kblocks_half + i;
                tma_load_3d(sS + slot * 32768, &p.tmA, 0, mt * 128, kb, barFull + 8 * slot);
                tma_load_3d(sS + slot * 32768 + 16384, &p.tmB, 0, kb * 64, nt * 2, barFull + 8 * slot);
            }
        }
    } else {
        const int wg = warp >> 2, wq = warp & 3;
        float acc[64];
        int prev = 0;
        for (int i = 0; i < p.kblocks_half; i++) {
            int slot = i % GS_NST;
            mbar_wait(barFull + 8 * slot, (i / GS_NST) & 1);
            wg_fence();
            uint64_t da = make_desc(sS + slot * 32768 + wg * 8192, 16, 1024);
            uint64_t db = make_desc(sS + slot * 32768 + 16384, 8192, 1024);
#pragma unroll
            for (int kk = 0; kk < 4; kk++)
                wgmma_m64n128k16_ss_tb(acc, da + (uint64_t)(kk * 2), db + (uint64_t)(kk * 128), (i | kk) != 0);
            wg_commit();
            if (i > 0) { wg_wait<1>(); if (lane == 0) mbar_arrive(barEmpty + 8 * prev); }
            prev = slot;
        }
        wg_wait<0>();
        const uint32_t peer = kh ^ 1;
        const uint32_t rbuf = mapa_u32(sR, peer), rbar = mapa_u32(barRed, peer);
        const int tw = threadIdx.x;
#pragma unroll
        for (int j = 0; j < 8; j++) {
            float a[4];
#pragma unroll
            for (int i = 0; i < 4; i++) a[i] = kh == 0 ? acc[(8 + j) * 4 + i] : acc[j * 4 + i];
            st_async_v4(rbuf + (j * 256 + tw) * 16, __float_as_uint(a[0]), __float_as_uint(a[1]), __float_as_uint(a[2]), __float_as_uint(a[3]), rbar);
        }
        mbar_wait(barRed, 0);
        named_bar_sync(1, 256);
        const uint32_t stage = sS + wg * 8192;
        const int mrow = wq * 16 + (lane & 7) + ((lane >> 3) & 1) * 8, mcolh = lane >> 4;
#pragma unroll
        for (int c = 0; c < 4; c++) {
            uint32_t r[4];
#pragma unroll
            for (int e = 0; e < 2; e++) {
                int j = c * 2 + e;
                float4 v;
                asm volatile("ld.shared.v4.f32 {%0,%1,%2,%3}, [%4];" : "=f"(v.x), "=f"(v.y), "=f"(v.z), "=f"(v.w) : "r"(sR + (j * 256 + tw) * 16) : "memory");
                float a[4];
#pragma unroll
                for (int i = 0; i < 4; i++) a[i] = kh == 0 ? acc[j * 4 + i] : acc[(8 + j) * 4 + i];
                r[e * 2 + 0] = pack_bf16(a[0] + v.x, a[1] + v.y);
                r[e * 2 + 1] = pack_bf16(a[2] + v.z, a[3] + v.w);
            }
            int chunk = (c * 2 + mcolh) ^ (mrow & 7);
            stmatrix_x4(stage + mrow * 128 + chunk * 16, r[0], r[1], r[2], r[3]);
        }
        fence_proxy_async_smem();
        named_bar_sync(2 + wg, 128);
        if ((threadIdx.x & 127) == 0) {
            tma_store_3d(&p.tmC, stage, 0, mt * 128 + wg * 64, p.c_col64 + nt * 2 + kh);
            bulk_commit();
            bulk_wait_read0();
        }
    }
    __syncthreads();
    cluster_sync_all();
}

typedef CUresult (*PFN_encodeTiled)(CUtensorMap*, CUtensorMapDataType, cuuint32_t, void*, const cuuint64_t*, const cuuint64_t*,
                                    const cuuint32_t*, const cuuint32_t*, CUtensorMapInterleave, CUtensorMapSwizzle,
                                    CUtensorMapL2promotion, CUtensorMapFloatOOBfill);
static PFN_encodeTiled g_encode = nullptr;
static void init_encode() {
    if (g_encode) return;
    void* fn = nullptr;
    cudaDriverEntryPointQueryResult st;
    cudaGetDriverEntryPoint("cuTensorMapEncodeTiled", &fn, cudaEnableDefault, &st);
    g_encode = (PFN_encodeTiled)fn;
}
static CUtensorMap make_tmap_3d64(const void* ptr, uint64_t rows, uint64_t cols, uint64_t ld, uint32_t box_rows, uint32_t box_c64) {
    CUtensorMap tm;
    cuuint64_t dims[3] = {64, rows, cols / 64};
    cuuint64_t strides[2] = {ld * 2, 128};
    cuuint32_t box[3] = {64, box_rows, box_c64};
    cuuint32_t es[3] = {1, 1, 1};
    g_encode(&tm, CU_TENSOR_MAP_DATA_TYPE_BFLOAT16, 3, (void*)ptr, dims, strides, box, es, CU_TENSOR_MAP_INTERLEAVE_NONE,
             CU_TENSOR_MAP_SWIZZLE_128B, CU_TENSOR_MAP_L2_PROMOTION_L2_128B, CU_TENSOR_MAP_FLOAT_OOB_FILL_NONE);
    return tm;
}

__device__ __align__(1024) bf16 g_qkvA[2048 * 1536];
__device__ __align__(1024) bf16 g_oA[2048 * 512];
__device__ __align__(1024) bf16 g_qkvB[2048 * 12288];
__device__ __align__(1024) bf16 g_kvmem[64 * 8 * 8192];
__device__ __align__(1024) bf16 g_oB[2048 * 4096];
__device__ __align__(1024) float g_part[2 * 64 * 32 * 64];
__device__ __align__(1024) uint4 g_membuf[64 * 512];
__device__ __align__(128) unsigned int g_flags[64];

__global__ void cleanup_kernel() {
    const int i = blockIdx.x * blockDim.x + threadIdx.x;
    const int n = gridDim.x * blockDim.x;
    uint4 z = make_uint4(0, 0, 0, 0);
    for (int k = i; k < 2 * 64 * 32 * 16; k += n) reinterpret_cast<uint4*>(g_part)[k] = z;
    for (int k = i; k < 64 * 512; k += n) g_membuf[k] = z;
    if (i < 64) g_flags[i] = 0u;
}

template <typename T> static T* sym_addr(T& sym) { void* p = nullptr; cudaGetSymbolAddress(&p, sym); return (T*)p; }

extern "C" void kernel_launch(void* const* d_in, const int* in_sizes, int n_in, void* d_out, int out_size) {
    const bf16* A_x = (const bf16*)d_in[0];
    const bf16* A_wqkv = (const bf16*)d_in[1];
    const bf16* A_wo = (const bf16*)d_in[2];
    const bf16* B_x = (const bf16*)d_in[3];
    const bf16* B_mem0 = (const bf16*)d_in[4];
    const bf16* B_Wq = (const bf16*)d_in[5];
    const bf16* B_Wk = (const bf16*)d_in[6];
    const bf16* B_Wv = (const bf16*)d_in[7];
    const bf16* B_Wo = (const bf16*)d_in[8];
    bf16* out = (bf16*)d_out;

    static bool inited = false;
    static cudaStream_t s1;
    static cudaEvent_t e_kv, e_s1;
    if (!inited) {
        init_encode();
        cudaFuncSetAttribute(gemm_w_kernel, cudaFuncAttributeMaxDynamicSharedMemorySize, GW_SMEM);
        cudaFuncSetAttribute(gemm_s_kernel, cudaFuncAttributeMaxDynamicSharedMemorySize, GS_SMEM);
        cudaFuncSetAttribute(chain_kernel, cudaFuncAttributeMaxDynamicSharedMemorySize, CH_SMEM);
        cudaFuncSetAttribute(attn_a_kernel, cudaFuncAttributeMaxDynamicSharedMemorySize, AA_SMEM);
        cudaFuncSetAttribute(attn_b_kernel, cudaFuncAttributeMaxDynamicSharedMemorySize, AB_SMEM);
        cudaStreamCreateWithFlags(&s1, cudaStreamNonBlocking);
        cudaEventCreateWithFlags(&e_kv, cudaEventDisableTiming);
        cudaEventCreateWithFlags(&e_s1, cudaEventDisableTiming);
        inited = true;
    }
    void *qkvA, *oA, *qkvB, *kvmem, *oB, *part, *membuf, *flags;
    cudaGetSymbolAddress(&qkvA, g_qkvA); cudaGetSymbolAddress(&oA, g_oA); cudaGetSymbolAddress(&qkvB, g_qkvB);
    cudaGetSymbolAddress(&kvmem, g_kvmem); cudaGetSymbolAddress(&oB, g_oB); cudaGetSymbolAddress(&part, g_part);
    cudaGetSymbolAddress(&membuf, g_membuf); cudaGetSymbolAddress(&flags, g_flags);
    cudaStream_t s0 = cudaStreamPerThread;

    GemmWParams pkv;
    pkv.tmA = make_tmap_3d64(B_x, 2048, 512, 512, 128, 1);
    pkv.tmB[0] = make_tmap_3d64(B_Wk, 512, 4096, 4096, 64, 2);
    pkv.tmB[1] = make_tmap_3d64(B_Wv, 512, 4096, 4096, 64, 2);
    pkv.tmB[2] = make_tmap_3d64(B_Wq, 512, 4096, 4096, 64, 2);
    pkv.tmC = make_tmap_3d64(qkvB, 2048, 12288, 12288, 128, 1);
    pkv.ntiles_per_mat = 32; pkv.c_col64[0] = 64; pkv.c_col64[1] = 128; pkv.c_col64[2] = 0;
    pkv.m_splits = 1; pkv.mtiles_per_cta = 16; pkv.flag_mats = 2; pkv.flags = (unsigned int*)flags;
    gemm_w_kernel<<<64, 384, GW_SMEM, s0>>>(pkv);
    cudaEventRecord(e_kv, s0);

    ChainParams pc;
    pc.tmW[0] = make_tmap_3d64(B_Wq, 512, 4096, 4096, 256, 1);
    pc.tmW[1] = make_tmap_3d64(B_Wk, 512, 4096, 4096, 256, 1);
    pc.tmW[2] = make_tmap_3d64(B_Wv, 512, 4096, 4096, 256, 1);
    pc.tmWo = make_tmap_3d64(B_Wo, 4096, 512, 512, 128, 1);
    pc.tmKV = make_tmap_3d64(qkvB, 2048, 12288, 12288, 32, 1);
    pc.mem0 = B_mem0; pc.kvmem = (bf16*)kvmem; pc.part = (float*)part; pc.membuf = (uint4*)membuf;
    pc.flags = (const unsigned int*)flags; pc.flag_target = 128; pc.dbg = nullptr;
    {
        cudaLaunchConfig_t cfg = {};
        cfg.gridDim = dim3(64); cfg.blockDim = dim3(384); cfg.dynamicSmemBytes = CH_SMEM; cfg.stream = s0;
        cudaLaunchAttribute at[2];
        at[0].id = cudaLaunchAttributeClusterDimension; at[0].val.clusterDim.x = 2; at[0].val.clusterDim.y = 1; at[0].val.clusterDim.z = 1;
        at[1].id = cudaLaunchAttributeProgrammaticStreamSerialization; at[1].val.programmaticStreamSerializationAllowed = 1;
        cfg.attrs = at; cfg.numAttrs = 2;
        cudaLaunchKernelEx(&cfg, chain_kernel, pc);
    }

    cudaStreamWaitEvent(s1, e_kv, 0);
    GemmWParams pq = pkv;
    pq.tmB[0] = pkv.tmB[2]; pq.c_col64[0] = 0; pq.m_splits = 2; pq.mtiles_per_cta = 8; pq.flag_mats = 0; pq.flags = nullptr;
    gemm_w_kernel<<<64, 384, GW_SMEM, s1>>>(pq);

    GemmWParams p1;
    p1.tmA = make_tmap_3d64(A_x, 2048, 512, 512, 128, 1);
    p1.tmB[0] = make_tmap_3d64(A_wqkv, 512, 1536, 1536, 64, 2); p1.tmB[1] = p1.tmB[0]; p1.tmB[2] = p1.tmB[0];
    p1.tmC = make_tmap_3d64(qkvA, 2048, 1536, 1536, 128, 1);
    p1.ntiles_per_mat = 12; p1.c_col64[0] = p1.c_col64[1] = p1.c_col64[2] = 0;
    p1.m_splits = 4; p1.mtiles_per_cta = 4; p1.flag_mats = 0; p1.flags = nullptr;
    gemm_w_kernel<<<48, 384, GW_SMEM, s1>>>(p1);

    AttnAParams pa;
    {
        cuuint64_t dims[2] = {1536, 2048}; cuuint64_t strides[1] = {3072}; cuuint32_t box[2] = {16, AA_KT}; cuuint32_t es[2] = {1, 1};
        g_encode(&pa.tmKV, CU_TENSOR_MAP_DATA_TYPE_BFLOAT16, 2, qkvA, dims, strides, box, es, CU_TENSOR_MAP_INTERLEAVE_NONE,
                 CU_TENSOR_MAP_SWIZZLE_32B, CU_TENSOR_MAP_L2_PROMOTION_L2_128B, CU_TENSOR_MAP_FLOAT_OOB_FILL_NONE);
    }
    pa.qkv = (const bf16*)qkvA; pa.o = (bf16*)oA;
    attn_a_kernel<<<256, 256, AA_SMEM, s1>>>(pa);

    GemmWParams p2;
    p2.tmA = make_tmap_3d64(oA, 2048, 512, 512, 128, 1);
    p2.tmB[0] = make_tmap_3d64(A_wo, 512, 512, 512, 64, 2); p2.tmB[1] = p2.tmB[0]; p2.tmB[2] = p2.tmB[0];
    p2.tmC = make_tmap_3d64(out, 2048, 1024, 1024, 128, 1);
    p2.ntiles_per_mat = 4; p2.c_col64[0] = p2.c_col64[1] = p2.c_col64[2] = 0;
    p2.m_splits = 16; p2.mtiles_per_cta = 1; p2.flag_mats = 0; p2.flags = nullptr;
    gemm_w_kernel<<<64, 384, GW_SMEM, s1>>>(p2);
    cudaEventRecord(e_s1, s1);

    cudaStreamWaitEvent(s0, e_s1, 0);
    AttnBParams pb;
    pb.tmQKV = make_tmap_3d64(qkvB, 2048, 12288, 12288, 32, 1);
    pb.tmKVM = make_tmap_3d64(kvmem, 512, 8192, 8192, 8, 1);
    pb.tmO = make_tmap_3d64(oB, 2048, 4096, 4096, 32, 1);
    pb.seg_flags = nullptr; pb.seg_target = 0;
    attn_b_kernel<<<512, 128, AB_SMEM, s0>>>(pb);
    cleanup_kernel<<<64, 256, 0, s0>>>();

    GemmSParams p4;
    p4.tmA = make_tmap_3d64(oB, 2048, 4096, 4096, 128, 1);
    p4.tmB = make_tmap_3d64(B_Wo, 4096, 512, 512, 64, 2);
    p4.tmC = make_tmap_3d64(out, 2048, 1024, 1024, 64, 1);
    p4.n_tiles = 4; p4.kblocks_half = 32; p4.c_col64 = 8;
    {
        cudaLaunchConfig_t cfg = {};
        cfg.gridDim = dim3(128); cfg.blockDim = dim3(288); cfg.dynamicSmemBytes = GS_SMEM; cfg.stream = s0;
        cudaLaunchAttribute at[1];
        at[0].id = cudaLaunchAttributeClusterDimension; at[0].val.clusterDim.x = 2; at[0].val.clusterDim.y = 1; at[0].val.clusterDim.z = 1;
        cfg.attrs = at; cfg.numAttrs = 1;
        cudaLaunchKernelEx(&cfg, gemm_s_kernel, p4);
    }
}
```

```cpp
#include <cuda_runtime.h>
#include <cuda_bf16.h>
#include <cuda.h>
#include <stdint.h>

typedef __nv_bfloat16 bf16;

__device__ __forceinline__ uint32_t smem_u32(const void* p) { return (uint32_t)__cvta_generic_to_shared(p); }
__device__ __forceinline__ void mbar_init(uint32_t bar, uint32_t cnt) {
    asm volatile("mbarrier.init.shared::cta.b64 [%0], %1;" :: "r"(bar), "r"(cnt) : "memory");
}
__device__ __forceinline__ void mbar_expect_tx(uint32_t bar, uint32_t bytes) {
    asm volatile("mbarrier.arrive.expect_tx.shared::cta.b64 _, [%0], %1;" :: "r"(bar), "r"(bytes) : "memory");
}
__device__ __forceinline__ void mbar_arrive(uint32_t bar) {
    asm volatile("mbarrier.arrive.shared::cta.b64 _, [%0];" :: "r"(bar) : "memory");
}
__device__ __forceinline__ bool mbar_try_wait(uint32_t bar, uint32_t parity) {
    uint32_t ok;
    asm volatile("{\n.reg .pred p;\nmbarrier.try_wait.parity.shared::cta.b64 p, [%1], %2;\nselp.u32 %0, 1, 0, p;\n}"
                 : "=r"(ok) : "r"(bar), "r"(parity) : "memory");
    return ok != 0;
}
__device__ __forceinline__ void mbar_wait(uint32_t bar, uint32_t parity) {
    uint32_t n = 0;
    while (!mbar_try_wait(bar, parity)) { if (++n > (1u << 20)) break; }
}
__device__ __forceinline__ void fence_proxy_async_smem() { asm volatile("fence.proxy.async.shared::cta;" ::: "memory"); }
__device__ __forceinline__ void fence_proxy_async_all() { asm volatile("fence.proxy.async;" ::: "memory"); }
__device__ __forceinline__ void fence_mbar_init() { asm volatile("fence.mbarrier_init.release.cluster;" ::: "memory"); }

__device__ __forceinline__ void tma_load_3d(uint32_t dst, const CUtensorMap* tm, int c0, int c1, int c2, uint32_t bar) {
    asm volatile("cp.async.bulk.tensor.3d.shared::cluster.global.mbarrier::complete_tx::bytes [%0], [%1, {%3, %4, %5}], [%2];"
                 :: "r"(dst), "l"(tm), "r"(bar), "r"(c0), "r"(c1), "r"(c2) : "memory");
}
__device__ __forceinline__ void tma_load_2d(uint32_t dst, const CUtensorMap* tm, int c0, int c1, uint32_t bar) {
    asm volatile("cp.async.bulk.tensor.2d.shared::cluster.global.mbarrier::complete_tx::bytes [%0], [%1, {%3, %4}], [%2];"
                 :: "r"(dst), "l"(tm), "r"(bar), "r"(c0), "r"(c1) : "memory");
}
__device__ __forceinline__ void tma_store_3d(const CUtensorMap* tm, uint32_t src, int c0, int c1, int c2) {
    asm volatile("cp.async.bulk.tensor.3d.global.shared::cta.bulk_group [%0, {%2, %3, %4}], [%1];"
                 :: "l"(tm), "r"(src), "r"(c0), "r"(c1), "r"(c2) : "memory");
}
__device__ __forceinline__ void bulk_commit() { asm volatile("cp.async.bulk.commit_group;" ::: "memory"); }
__device__ __forceinline__ void bulk_wait_read0() { asm volatile("cp.async.bulk.wait_group.read 0;" ::: "memory"); }
__device__ __forceinline__ void bulk_wait_all0() { asm volatile("cp.async.bulk.wait_group 0;" ::: "memory"); }
__device__ __forceinline__ void prefetch_tmap(const CUtensorMap* tm) {
    asm volatile("prefetch.tensormap [%0];" :: "l"(tm) : "memory");
}

__device__ __forceinline__ void wg_fence() { asm volatile("wgmma.fence.sync.aligned;" ::: "memory"); }
__device__ __forceinline__ void wg_commit() { asm volatile("wgmma.commit_group.sync.aligned;" ::: "memory"); }
template <int N> __device__ __forceinline__ void wg_wait() { asm volatile("wgmma.wait_group.sync.aligned %0;" :: "n"(N) : "memory"); }

__device__ __forceinline__ void named_bar_sync(int id, int nthreads) {
    asm volatile("bar.sync %0, %1;" :: "r"(id), "r"(nthreads) : "memory");
}
__device__ __forceinline__ void named_bar_arrive(int id, int nthreads) {
    asm volatile("bar.arrive %0, %1;" :: "r"(id), "r"(nthreads) : "memory");
}

__device__ __forceinline__ uint64_t make_desc(uint32_t saddr, uint32_t lbo_bytes, uint32_t sbo_bytes) {
    return (uint64_t)((saddr & 0x3FFFF) >> 4) | ((uint64_t)(lbo_bytes >> 4) << 16) | ((uint64_t)(sbo_bytes >> 4) << 32) | ((uint64_t)1 << 62);
}

__device__ __forceinline__ uint32_t pack_bf16(float lo, float hi) {
    uint32_t r;
    asm("cvt.rn.bf16x2.f32 %0, %1, %2;" : "=r"(r) : "f"(hi), "f"(lo));
    return r;
}
__device__ __forceinline__ void stmatrix_x4(uint32_t addr, uint32_t r0, uint32_t r1, uint32_t r2, uint32_t r3) {
    asm volatile("stmatrix.sync.aligned.m8n8.x4.shared.b16 [%0], {%1,%2,%3,%4};" :: "r"(addr), "r"(r0), "r"(r1), "r"(r2), "r"(r3) : "memory");
}
__device__ __forceinline__ void ldmatrix_x4(uint32_t& r0, uint32_t& r1, uint32_t& r2, uint32_t& r3, uint32_t addr) {
    asm volatile("ldmatrix.sync.aligned.m8n8.x4.shared.b16 {%0,%1,%2,%3}, [%4];" : "=r"(r0), "=r"(r1), "=r"(r2), "=r"(r3) : "r"(addr) : "memory");
}
__device__ __forceinline__ void ldmatrix_x4_t(uint32_t& r0, uint32_t& r1, uint32_t& r2, uint32_t& r3, uint32_t addr) {
    asm volatile("ldmatrix.sync.aligned.m8n8.x4.trans.shared.b16 {%0,%1,%2,%3}, [%4];" : "=r"(r0), "=r"(r1), "=r"(r2), "=r"(r3) : "r"(addr) : "memory");
}
__device__ __forceinline__ void ldmatrix_x2(uint32_t& r0, uint32_t& r1, uint32_t addr) {
    asm volatile("ldmatrix.sync.aligned.m8n8.x2.shared.b16 {%0,%1}, [%2];" : "=r"(r0), "=r"(r1) : "r"(addr) : "memory");
}
__device__ __forceinline__ void ldmatrix_x2_t(uint32_t& r0, uint32_t& r1, uint32_t addr) {
    asm volatile("ldmatrix.sync.aligned.m8n8.x2.trans.shared.b16 {%0,%1}, [%2];" : "=r"(r0), "=r"(r1) : "r"(addr) : "memory");
}
__device__ __forceinline__ void mma16816(float* c, const uint32_t* a, uint32_t b0, uint32_t b1) {
    asm volatile("mma.sync.aligned.m16n8k16.row.col.f32.bf16.bf16.f32 {%0,%1,%2,%3}, {%4,%5,%6,%7}, {%8,%9}, {%0,%1,%2,%3};"
                 : "+f"(c[0]), "+f"(c[1]), "+f"(c[2]), "+f"(c[3]) : "r"(a[0]), "r"(a[1]), "r"(a[2]), "r"(a[3]), "r"(b0), "r"(b1));
}

__device__ __forceinline__ void wgmma_m64n128k16_ss_tb(float* d, uint64_t da, uint64_t db, int scale_d) {
    asm volatile(
        "{\n.reg .pred p;\nsetp.ne.b32 p, %66, 0;\n"
        "wgmma.mma_async.sync.aligned.m64n128k16.f32.bf16.bf16 "
        "{%0,%1,%2,%3,%4,%5,%6,%7,%8,%9,%10,%11,%12,%13,%14,%15,"
        "%16,%17,%18,%19,%20,%21,%22,%23,%24,%25,%26,%27,%28,%29,%30,%31,"
        "%32,%33,%34,%35,%36,%37,%38,%39,%40,%41,%42,%43,%44,%45,%46,%47,"
        "%48,%49,%50,%51,%52,%53,%54,%55,%56,%57,%58,%59,%60,%61,%62,%63},"
        " %64, %65, p, 1, 1, 0, 1;\n}\n"
        : "+f"(d[0]), "+f"(d[1]), "+f"(d[2]), "+f"(d[3]), "+f"(d[4]), "+f"(d[5]), "+f"(d[6]), "+f"(d[7]),
          "+f"(d[8]), "+f"(d[9]), "+f"(d[10]), "+f"(d[11]), "+f"(d[12]), "+f"(d[13]), "+f"(d[14]), "+f"(d[15]),
          "+f"(d[16]), "+f"(d[17]), "+f"(d[18]), "+f"(d[19]), "+f"(d[20]), "+f"(d[21]), "+f"(d[22]), "+f"(d[23]),
          "+f"(d[24]), "+f"(d[25]), "+f"(d[26]), "+f"(d[27]), "+f"(d[28]), "+f"(d[29]), "+f"(d[30]), "+f"(d[31]),
          "+f"(d[32]), "+f"(d[33]), "+f"(d[34]), "+f"(d[35]), "+f"(d[36]), "+f"(d[37]), "+f"(d[38]), "+f"(d[39]),
          "+f"(d[40]), "+f"(d[41]), "+f"(d[42]), "+f"(d[43]), "+f"(d[44]), "+f"(d[45]), "+f"(d[46]), "+f"(d[47]),
          "+f"(d[48]), "+f"(d[49]), "+f"(d[50]), "+f"(d[51]), "+f"(d[52]), "+f"(d[53]), "+f"(d[54]), "+f"(d[55]),
          "+f"(d[56]), "+f"(d[57]), "+f"(d[58]), "+f"(d[59]), "+f"(d[60]), "+f"(d[61]), "+f"(d[62]), "+f"(d[63])
        : "l"(da), "l"(db), "r"(scale_d));
}

__device__ __forceinline__ void wgmma_m64n128k16_rs(float* d, const uint32_t* a, uint64_t db, int scale_d) {
    asm volatile(
        "{\n.reg .pred p;\nsetp.ne.b32 p, %69, 0;\n"
        "wgmma.mma_async.sync.aligned.m64n128k16.f32.bf16.bf16 "
        "{%0,%1,%2,%3,%4,%5,%6,%7,%8,%9,%10,%11,%12,%13,%14,%15,"
        "%16,%17,%18,%19,%20,%21,%22,%23,%24,%25,%26,%27,%28,%29,%30,%31,"
        "%32,%33,%34,%35,%36,%37,%38,%39,%40,%41,%42,%43,%44,%45,%46,%47,"
        "%48,%49,%50,%51,%52,%53,%54,%55,%56,%57,%58,%59,%60,%61,%62,%63},"
        " {%64,%65,%66,%67}, %68, p, 1, 1, 0;\n}\n"
        : "+f"(d[0]), "+f"(d[1]), "+f"(d[2]), "+f"(d[3]), "+f"(d[4]), "+f"(d[5]), "+f"(d[6]), "+f"(d[7]),
          "+f"(d[8]), "+f"(d[9]), "+f"(d[10]), "+f"(d[11]), "+f"(d[12]), "+f"(d[13]), "+f"(d[14]), "+f"(d[15]),
          "+f"(d[16]), "+f"(d[17]), "+f"(d[18]), "+f"(d[19]), "+f"(d[20]), "+f"(d[21]), "+f"(d[22]), "+f"(d[23]),
          "+f"(d[24]), "+f"(d[25]), "+f"(d[26]), "+f"(d[27]), "+f"(d[28]), "+f"(d[29]), "+f"(d[30]), "+f"(d[31]),
          "+f"(d[32]), "+f"(d[33]), "+f"(d[34]), "+f"(d[35]), "+f"(d[36]), "+f"(d[37]), "+f"(d[38]), "+f"(d[39]),
          "+f"(d[40]), "+f"(d[41]), "+f"(d[42]), "+f"(d[43]), "+f"(d[44]), "+f"(d[45]), "+f"(d[46]), "+f"(d[47]),
          "+f"(d[48]), "+f"(d[49]), "+f"(d[50]), "+f"(d[51]), "+f"(d[52]), "+f"(d[53]), "+f"(d[54]), "+f"(d[55]),
          "+f"(d[56]), "+f"(d[57]), "+f"(d[58]), "+f"(d[59]), "+f"(d[60]), "+f"(d[61]), "+f"(d[62]), "+f"(d[63])
        : "r"(a[0]), "r"(a[1]), "r"(a[2]), "r"(a[3]), "l"(db), "r"(scale_d));
}
__device__ __forceinline__ void stmatrix_x4_t(uint32_t addr, uint32_t r0, uint32_t r1, uint32_t r2, uint32_t r3) {
    asm volatile("stmatrix.sync.aligned.m8n8.x4.trans.shared.b16 [%0], {%1,%2,%3,%4};" :: "r"(addr), "r"(r0), "r"(r1), "r"(r2), "r"(r3) : "memory");
}
template <int R> __device__ __forceinline__ void reg_alloc() { asm volatile("setmaxnreg.inc.sync.aligned.u32 %0;" :: "n"(R)); }
template <int R> __device__ __forceinline__ void reg_dealloc() { asm volatile("setmaxnreg.dec.sync.aligned.u32 %0;" :: "n"(R)); }

struct GemmWParams {
    CUtensorMap tmA;
    CUtensorMap tmB[3];
    CUtensorMap tmC;
    int ntiles_per_mat;
    int c_col64[3];
    int m_splits;
    int mtiles_per_cta;
    int flag_mats;
    unsigned int* flags;
};

constexpr int GW_NST = 11;
constexpr int GW_SMEM = GW_NST * 16384 + 32768 + 256;

__global__ void __launch_bounds__(384, 1) gemm_w_kernel(const __grid_constant__ GemmWParams p) {
    extern __shared__ __align__(1024) unsigned char smem[];
    const uint32_t sA = smem_u32(smem);
    const uint32_t sOut = sA + GW_NST * 16384;
    const uint32_t bars = sOut + 32768;
    const uint32_t barFull = bars, barEmpty = bars + 8 * GW_NST;
    const int warp = __shfl_sync(0xffffffff, threadIdx.x >> 5, 0), lane = threadIdx.x & 31;

    const int gnt = blockIdx.x / p.m_splits;
    const int ms = blockIdx.x % p.m_splits;
    const int mat = gnt / p.ntiles_per_mat;
    const int nt = gnt % p.ntiles_per_mat;
    const int tile0 = ms * p.mtiles_per_cta;
    const int ntl = p.mtiles_per_cta;

    if (threadIdx.x == 0) {
        for (int i = 0; i < GW_NST; i++) { mbar_init(barFull + 8 * i, 1); mbar_init(barEmpty + 8 * i, 8); }
        fence_mbar_init();
    }
    __syncthreads();

    const int wgi = __shfl_sync(0xffffffff, threadIdx.x >> 7, 0);
    asm volatile("griddepcontrol.launch_dependents;" ::: "memory");
    if (wgi == 0) {
        reg_dealloc<40>();
        if (warp == 0 && lane == 0) {
            const CUtensorMap* tmB = &p.tmB[mat];
            const int total = 8 + ntl * 8;
            for (int idx = 0; idx < total; idx++) {
                int slot = idx % GW_NST;
                if (idx >= GW_NST) mbar_wait(barEmpty + 8 * slot, ((idx / GW_NST) - 1) & 1);
                mbar_expect_tx(barFull + 8 * slot, 16384);
                if (idx < 8) tma_load_3d(sA + slot * 16384, tmB, 0, idx * 64, nt * 2, barFull + 8 * slot);
                else {
                    int t = (idx - 8) >> 3, j = (idx - 8) & 7;
                    tma_load_3d(sA + slot * 16384, &p.tmA, 0, (tile0 + t) * 128, j, barFull + 8 * slot);
                }
            }
        }
    } else {
        reg_alloc<232>();
        const int wg = (warp >> 2) - 1, wq = warp & 3;
        uint32_t w[32][4];
        float acc[64];
        {
            const int krow = (lane & 7) + ((lane >> 4) & 1) * 8;
            const int chunk = wq * 2 + ((lane >> 3) & 1);
#pragma unroll
            for (int kb = 0; kb < 8; kb++) {
                mbar_wait(barFull + 8 * kb, 0);
#pragma unroll
                for (int kk = 0; kk < 4; kk++) {
                    int r = kk * 16 + krow;
                    uint32_t addr = sA + kb * 16384 + wg * 8192 + r * 128 + ((chunk ^ (r & 7)) << 4);
                    ldmatrix_x4_t(w[kb * 4 + kk][0], w[kb * 4 + kk][1], w[kb * 4 + kk][2], w[kb * 4 + kk][3], addr);
                }
                __syncwarp();
                if (lane == 0) mbar_arrive(barEmpty + 8 * kb);
            }
        }
        const bool do_flag = (p.flags != nullptr) && (mat < p.flag_mats);
        const int tid_wg = threadIdx.x & 127;
        int pend_tile = -1;
        int idx = 8;
        for (int t = 0; t < ntl; t++) {
            int prev_slot = 0;
            if (wg == 0) { if (t > 0) named_bar_sync(3, 256); }
            else named_bar_sync(4, 256);
#pragma unroll
            for (int j = 0; j < 8; j++, idx++) {
                int slot = idx % GW_NST;
                mbar_wait(barFull + 8 * slot, (idx / GW_NST) & 1);
                wg_fence();
                uint64_t db = make_desc(sA + slot * 16384, 16, 1024);
#pragma unroll
                for (int kk = 0; kk < 4; kk++)
                    wgmma_m64n128k16_rs(acc, w[j * 4 + kk], db + (uint64_t)(kk * 2), (j | kk) != 0);
                wg_commit();
                if (j == 7) {
                    if (wg == 0) named_bar_arrive(4, 256);
                    else if (t + 1 < ntl) named_bar_arrive(3, 256);
                }
                if (j > 0) {
                    wg_wait<1>();
                    if (lane == 0) mbar_arrive(barEmpty + 8 * prev_slot);
                }
                prev_slot = slot;
            }
            wg_wait<0>();
            if (lane == 0) mbar_arrive(barEmpty + 8 * prev_slot);
            if (tid_wg == 0 && pend_tile >= 0) {
                if (do_flag) {
                    bulk_wait_all0();
                    fence_proxy_async_all();
                    __threadfence();
                    atomicAdd(p.flags + pend_tile, 1u);
                } else bulk_wait_read0();
            }
            named_bar_sync(1 + wg, 128);
            const uint32_t sbase = sOut + wg * 16384;
            const int mid = lane >> 3;
            const int chunk = wq * 2 + (mid & 1);
#pragma unroll
            for (int nb = 0; nb < 8; nb++) {
                const int a0 = nb * 8;
                uint32_t r0 = pack_bf16(acc[a0 + 0], acc[a0 + 1]);
                uint32_t r1 = pack_bf16(acc[a0 + 2], acc[a0 + 3]);
                uint32_t r2 = pack_bf16(acc[a0 + 4], acc[a0 + 5]);
                uint32_t r3 = pack_bf16(acc[a0 + 6], acc[a0 + 7]);
                int tok = nb * 16 + (mid >> 1) * 8 + (lane & 7);
                stmatrix_x4_t(sbase + tok * 128 + ((chunk ^ (tok & 7)) << 4), r0, r1, r2, r3);
            }
            fence_proxy_async_smem();
            named_bar_sync(1 + wg, 128);
            if (tid_wg == 0) {
                tma_store_3d(&p.tmC, sbase, 0, (tile0 + t) * 128, p.c_col64[mat] + nt * 2 + wg);
                bulk_commit();
            }
            pend_tile = tile0 + t;
        }
        if (pend_tile >= 0 && tid_wg == 0) {
            bulk_wait_all0();
            if (do_flag) {
                fence_proxy_async_all();
                __threadfence();
                atomicAdd(p.flags + pend_tile, 1u);
            }
        }
    }
}

#define NSTEPS 64
#define POLL_B 1
#define POLL_R 1
struct ChainParams {
    CUtensorMap tmW[3];
    CUtensorMap tmWo;
    CUtensorMap tmKV;
    const bf16* mem0;
    bf16* kvmem;
    float* part;
    uint4* membuf;
    const unsigned int* flags;
    unsigned int flag_target;
    unsigned int* seg_flags;
    long long* dbg;
};

constexpr int CH_MEM_STRIDE = 1040;
constexpr int CH_Q_STRIDE = 144;
constexpr int CH_O_STRIDE = 272;
constexpr int CH_NKV = 4;
constexpr int CH_KV_BYTES = 15360;
constexpr int CH_OFF_WO = 0;
constexpr int CH_OFF_WV = 65536;
constexpr int CH_OFF_KV = 131072;
constexpr int CH_OFF_MEM = CH_OFF_KV + CH_NKV * CH_KV_BYTES;
constexpr int CH_OFF_Q = CH_OFF_MEM + 8320;
constexpr int CH_OFF_O = CH_OFF_Q + 1152;
constexpr int CH_OFF_RED1 = CH_OFF_O + 2176;
constexpr int CH_OFF_SC = CH_OFF_RED1 + 6144;
constexpr int CH_OFF_RED2 = CH_OFF_SC + 1280;
constexpr int CH_OFF_ZERO = CH_OFF_RED2 + 2048;
constexpr int CH_OFF_BAR = CH_OFF_ZERO + 128;
constexpr int CH_SMEM = CH_OFF_BAR + 256;

__device__ __forceinline__ uint32_t mapa_u32(uint32_t addr, uint32_t rank) {
    uint32_t r; asm volatile("mapa.shared::cluster.u32 %0, %1, %2;" : "=r"(r) : "r"(addr), "r"(rank)); return r;
}
__device__ __forceinline__ void st_async_v4(uint32_t addr, uint32_t a, uint32_t b, uint32_t c, uint32_t d, uint32_t mbar) {
    asm volatile("st.async.shared::cluster.mbarrier::complete_tx::bytes.v4.b32 [%0], {%1,%2,%3,%4}, [%5];"
                 :: "r"(addr), "r"(a), "r"(b), "r"(c), "r"(d), "r"(mbar) : "memory");
}
__device__ __forceinline__ void st_async_v2(uint32_t addr, uint32_t a, uint32_t b, uint32_t mbar) {
    asm volatile("st.async.shared::cluster.mbarrier::complete_tx::bytes.v2.b32 [%0], {%1,%2}, [%3];"
                 :: "r"(addr), "r"(a), "r"(b), "r"(mbar) : "memory");
}
__device__ __forceinline__ bool mbar_try_wait_cl(uint32_t bar, uint32_t parity) {
    uint32_t ok;
    asm volatile("{\n.reg .pred p;\nmbarrier.try_wait.parity.acquire.cluster.shared::cta.b64 p, [%1], %2;\nselp.u32 %0, 1, 0, p;\n}"
                 : "=r"(ok) : "r"(bar), "r"(parity) : "memory");
    return ok != 0;
}
__device__ __forceinline__ void mbar_wait_cl(uint32_t bar, uint32_t parity) {
    uint32_t n = 0;
    while (!mbar_try_wait_cl(bar, parity)) { if (++n > (1u << 20)) break; }
}
__device__ __forceinline__ void cluster_sync_all() {
    asm volatile("barrier.cluster.arrive.aligned;\nbarrier.cluster.wait.aligned;" ::: "memory");
}
__device__ __forceinline__ uint4 ld_relaxed_v4(const void* p) {
    uint4 v;
    asm volatile("ld.relaxed.gpu.global.v4.u32 {%0,%1,%2,%3}, [%4];" : "=r"(v.x), "=r"(v.y), "=r"(v.z), "=r"(v.w) : "l"(p) : "memory");
    return v;
}
__device__ __forceinline__ void st_relaxed_v4(void* p, uint32_t a, uint32_t b, uint32_t c, uint32_t d) {
    asm volatile("st.relaxed.gpu.global.v4.u32 [%0], {%1,%2,%3,%4};" :: "l"(p), "r"(a), "r"(b), "r"(c), "r"(d) : "memory");
}
__device__ __forceinline__ unsigned int ld_acquire_u32(const unsigned int* p) {
    unsigned int v;
    asm volatile("ld.acquire.gpu.global.u32 %0, [%1];" : "=r"(v) : "l"(p) : "memory");
    return v;
}
__device__ __forceinline__ void lds128(uint32_t* r, uint32_t addr) {
    asm volatile("ld.shared.v4.u32 {%0,%1,%2,%3}, [%4];" : "=r"(r[0]), "=r"(r[1]), "=r"(r[2]), "=r"(r[3]) : "r"(addr) : "memory");
}
__device__ __forceinline__ float ex2_approx(float x) { float y; asm("ex2.approx.ftz.f32 %0, %1;" : "=f"(y) : "f"(x)); return y; }
__device__ __forceinline__ void mma_nv(float* c, const uint32_t* a, uint32_t b0, uint32_t b1) {
    asm("mma.sync.aligned.m16n8k16.row.col.f32.bf16.bf16.f32 {%0,%1,%2,%3}, {%4,%5,%6,%7}, {%8,%9}, {%0,%1,%2,%3};"
        : "+f"(c[0]), "+f"(c[1]), "+f"(c[2]), "+f"(c[3]) : "r"(a[0]), "r"(a[1]), "r"(a[2]), "r"(a[3]), "r"(b0), "r"(b1));
}

__device__ __forceinline__ void st_relaxed_v2(void* p, uint32_t a, uint32_t b) {
    asm volatile("st.relaxed.gpu.global.v2.u32 [%0], {%1,%2};" :: "l"(p), "r"(a), "r"(b) : "memory");
}

__global__ void __launch_bounds__(384, 1) chain_kernel(const __grid_constant__ ChainParams p) {
    extern __shared__ __align__(1024) unsigned char smem[];
    const uint32_t sb = smem_u32(smem);
    int tid; asm volatile("mov.u32 %0, %%tid.x;" : "=r"(tid));
    int bid; asm volatile("mov.u32 %0, %%ctaid.x;" : "=r"(bid));
    const int lane = tid & 31;
    const int warp = __shfl_sync(0xffffffff, tid >> 5, 0);
    const int wgi = __shfl_sync(0xffffffff, tid >> 7, 0);
    const int head = bid >> 1, half = bid & 1;
    const uint32_t barSc = sb + CH_OFF_BAR, barV = barSc + 8, barLd = barSc + 16, barKV = barSc + 24;

    if (tid == 0) {
        mbar_init(barSc, 1); mbar_init(barV, 1); mbar_init(barLd, 1);
        for (int i = 0; i < CH_NKV; i++) mbar_init(barKV + 8 * i, 1);
        fence_mbar_init();
        mbar_expect_tx(barSc, 1280);
        mbar_expect_tx(barV, 1024);
    }
    if (tid < 32) *reinterpret_cast<uint32_t*>(smem + CH_OFF_ZERO + tid * 4) = 0u;
    __syncthreads();
    cluster_sync_all();
    const uint32_t peer = half ^ 1;
    const int t4 = lane & 3, g8 = lane >> 2;
    const int lr = lane & 7, lm = lane >> 3;

    if (wgi < 2) {
        reg_alloc<208>();
        const int g = warp >> 1, kh = warp & 1;
        uint32_t wqk[2][16][4];
        {
            const int c64 = head * 2 + half;
            const int krow = lr + ((lane >> 4) & 1) * 8;
            const int chunk = g * 2 + (lm & 1);
            if (tid == 0) {
                mbar_expect_tx(barLd, 131072);
                tma_load_3d(sb + CH_OFF_WO, &p.tmW[0], 0, 0, c64, barLd);
                tma_load_3d(sb + CH_OFF_WO + 32768, &p.tmW[0], 0, 256, c64, barLd);
                tma_load_3d(sb + CH_OFF_WV, &p.tmW[1], 0, 0, c64, barLd);
                tma_load_3d(sb + CH_OFF_WV + 32768, &p.tmW[1], 0, 256, c64, barLd);
            }
            mbar_wait(barLd, 0);
#pragma unroll
            for (int m = 0; m < 2; m++)
#pragma unroll
                for (int ks = 0; ks < 16; ks++) {
                    int r = kh * 256 + ks * 16 + krow;
                    uint32_t addr = sb + (m == 0 ? CH_OFF_WO : CH_OFF_WV) + r * 128 + ((chunk ^ (r & 7)) << 4);
                    ldmatrix_x4_t(wqk[m][ks][0], wqk[m][ks][1], wqk[m][ks][2], wqk[m][ks][3], addr);
                }
            named_bar_sync(7, 256);
            if (tid == 0) {
                mbar_expect_tx(barLd, 131072);
                tma_load_3d(sb + CH_OFF_WV, &p.tmW[2], 0, 0, c64, barLd);
                tma_load_3d(sb + CH_OFF_WV + 32768, &p.tmW[2], 0, 256, c64, barLd);
                for (int i = 0; i < 4; i++) tma_load_3d(sb + CH_OFF_WO + i * 16384, &p.tmWo, 0, head * 128, half * 4 + i, barLd);
            }
            mbar_wait(barLd, 1);
            uint32_t f[16][4];
#pragma unroll
            for (int ks = 0; ks < 16; ks++) {
                int r = kh * 256 + ks * 16 + krow;
                ldmatrix_x4_t(f[ks][0], f[ks][1], f[ks][2], f[ks][3], sb + CH_OFF_WV + r * 128 + ((chunk ^ (r & 7)) << 4));
            }
            named_bar_sync(7, 256);
#pragma unroll
            for (int ks = 0; ks < 16; ks++)
                asm volatile("st.shared.v4.u32 [%0], {%1,%2,%3,%4};" :: "r"(sb + CH_OFF_WV + ((warp * 16 + ks) * 32 + lane) * 16), "r"(f[ks][0]), "r"(f[ks][1]), "r"(f[ks][2]), "r"(f[ks][3]) : "memory");
#pragma unroll
            for (int ks = 0; ks < 8; ks++)
#pragma unroll
                for (int mt = 0; mt < 2; mt++) {
                    int r = ks * 16 + krow;
                    int colchunk = warp * 4 + mt * 2 + (lm & 1);
                    ldmatrix_x4_t(f[ks * 2 + mt][0], f[ks * 2 + mt][1], f[ks * 2 + mt][2], f[ks * 2 + mt][3],
                                  sb + CH_OFF_WO + (colchunk >> 3) * 16384 + r * 128 + (((colchunk & 7) ^ (r & 7)) << 4));
                }
            named_bar_sync(7, 256);
#pragma unroll
            for (int i = 0; i < 16; i++)
                asm volatile("st.shared.v4.u32 [%0], {%1,%2,%3,%4};" :: "r"(sb + CH_OFF_WO + ((warp * 16 + i) * 32 + lane) * 16), "r"(f[i][0]), "r"(f[i][1]), "r"(f[i][2]), "r"(f[i][3]) : "memory");
            named_bar_sync(7, 256);
        }
        const uint32_t wvbase = sb + CH_OFF_WV + (warp * 16 * 32 + lane) * 16;
        const uint32_t wobase = sb + CH_OFF_WO + (warp * 16 * 32 + lane) * 16;
        const uint32_t bAddr = sb + CH_OFF_MEM + lr * CH_MEM_STRIDE + (kh * 256 + lm * 8) * 2;
        const uint32_t memDst = sb + CH_OFF_MEM + (tid & 7) * CH_MEM_STRIDE + (tid >> 3) * 16;
        const uint32_t redMine = sb + CH_OFF_RED1 + warp * 512 + lane * 16, redOther = sb + CH_OFF_RED1 + (warp ^ 1) * 512 + lane * 16;
        const uint32_t redV = sb + CH_OFF_RED1 + 4096 + g * 512 + lane * 16;
        const uint32_t qDst = sb + CH_OFF_Q + lr * CH_Q_STRIDE + (g * 16 + (lm & 1) * 8) * 2;
        const uint32_t kvOff = lr * 128 + (((g * 2 + (lm & 1)) ^ lr) << 4);
        const uint32_t peerBase = mapa_u32(sb, peer) - sb;
        const uint32_t oAddr = sb + CH_OFF_O + lr * CH_O_STRIDE + lm * 16;
        const uint4* memSrc = p.membuf + tid;
        float* partW = p.part + ((size_t)(half * 32 + warp * 4) * 32 + head) * 64 + lane * 2;
        const float* partR = p.part + (size_t)bid * (32 * 64) + tid * 4;
        uint4* memOut = p.membuf + bid * 8 + g8;

        for (int s = 0; s < NSTEPS; s++) {
            const uint32_t sKV = sb + CH_OFF_KV + (s & (CH_NKV - 1)) * CH_KV_BYTES;
            uint32_t wv[16][4];
#pragma unroll
            for (int i = 0; i < 12; i++) lds128(wv[i], wvbase + i * 512);
            {
                uint4 v0, v1;
                if (s == 0) {
                    v0 = *reinterpret_cast<const uint4*>(p.mem0 + (tid & 7) * 512 + (tid >> 3) * 8);
                    v1 = *reinterpret_cast<const uint4*>(p.mem0 + (tid & 7) * 512 + ((tid >> 3) + 32) * 8);
                } else {
                    const uint4* src = memSrc + (s - 1) * 512;
                    uint32_t n = 0;
                    do { v0 = ld_relaxed_v4(src); v1 = ld_relaxed_v4(src + 256); } while (POLL_B && (v0.x == 0u || v1.x == 0u) && ++n < (1u << 22));
                }
                asm volatile("st.shared.v4.u32 [%0], {%1,%2,%3,%4};" :: "r"(memDst), "r"(v0.x), "r"(v0.y), "r"(v0.z), "r"(v0.w) : "memory");
                asm volatile("st.shared.v4.u32 [%0], {%1,%2,%3,%4};" :: "r"(memDst + 512), "r"(v1.x), "r"(v1.y), "r"(v1.z), "r"(v1.w) : "memory");
            }
            named_bar_sync(7, 256);
            {
                float aq[2][4], ak[2][4];
#pragma unroll
                for (int i = 0; i < 4; i++) { aq[0][i] = aq[1][i] = ak[0][i] = ak[1][i] = 0.f; }
#pragma unroll
                for (int hb = 0; hb < 4; hb++) {
                    uint32_t b[2][4];
#pragma unroll
                    for (int kk = 0; kk < 2; kk++) ldmatrix_x4(b[kk][0], b[kk][1], b[kk][2], b[kk][3], bAddr + (hb * 2 + kk) * 64);
#pragma unroll
                    for (int kk = 0; kk < 2; kk++) {
                        const int k2 = (hb * 2 + kk) * 2;
                        mma_nv(aq[0], wqk[0][k2], b[kk][0], b[kk][1]);
                        mma_nv(ak[0], wqk[1][k2], b[kk][0], b[kk][1]);
                        mma_nv(aq[1], wqk[0][k2 + 1], b[kk][2], b[kk][3]);
                        mma_nv(ak[1], wqk[1][k2 + 1], b[kk][2], b[kk][3]);
                    }
                }
                float gv[4], kp[4];
#pragma unroll
                for (int i = 0; i < 4; i++) {
                    float q = aq[0][i] + aq[1][i], k = ak[0][i] + ak[1][i];
                    gv[i] = kh == 0 ? k : q;
                    kp[i] = kh == 0 ? q : k;
                }
                asm volatile("st.shared.v4.f32 [%0], {%1,%2,%3,%4};" :: "r"(redMine), "f"(gv[0]), "f"(gv[1]), "f"(gv[2]), "f"(gv[3]) : "memory");
                named_bar_sync(1 + g, 64);
                float o0, o1, o2, o3;
                asm volatile("ld.shared.v4.f32 {%0,%1,%2,%3}, [%4];" : "=f"(o0), "=f"(o1), "=f"(o2), "=f"(o3) : "r"(redOther) : "memory");
                uint32_t r0 = pack_bf16(kp[0] + o0, kp[1] + o1);
                uint32_t r1 = pack_bf16(kp[2] + o2, kp[3] + o3);
                asm volatile("stmatrix.sync.aligned.m8n8.x2.trans.shared.b16 [%0], {%1,%2};" :: "r"(kh == 0 ? qDst : sKV + kvOff), "r"(r0), "r"(r1) : "memory");
            }
            named_bar_arrive(5, 384);
            {
                float av[2][4];
#pragma unroll
                for (int i = 0; i < 4; i++) { av[0][i] = av[1][i] = 0.f; }
#pragma unroll
                for (int i = 12; i < 16; i++) lds128(wv[i], wvbase + i * 512);
#pragma unroll
                for (int hb = 0; hb < 2; hb++) {
                    uint32_t b[4][4];
#pragma unroll
                    for (int kk = 0; kk < 4; kk++) ldmatrix_x4(b[kk][0], b[kk][1], b[kk][2], b[kk][3], bAddr + (hb * 4 + kk) * 64);
#pragma unroll
                    for (int kk = 0; kk < 4; kk++) {
                        mma_nv(av[0], wv[(hb * 4 + kk) * 2], b[kk][0], b[kk][1]);
                        mma_nv(av[1], wv[(hb * 4 + kk) * 2 + 1], b[kk][2], b[kk][3]);
                    }
                }
#pragma unroll
                for (int i = 0; i < 4; i++) av[0][i] += av[1][i];
                if (kh == 1)
                    asm volatile("st.shared.v4.f32 [%0], {%1,%2,%3,%4};" :: "r"(redV), "f"(av[0][0]), "f"(av[0][1]), "f"(av[0][2]), "f"(av[0][3]) : "memory");
                named_bar_sync(1 + g, 64);
                if (kh == 0) {
                    float o0, o1, o2, o3;
                    asm volatile("ld.shared.v4.f32 {%0,%1,%2,%3}, [%4];" : "=f"(o0), "=f"(o1), "=f"(o2), "=f"(o3) : "r"(redV) : "memory");
                    uint32_t r0 = pack_bf16(av[0][0] + o0, av[0][1] + o1);
                    uint32_t r1 = pack_bf16(av[0][2] + o2, av[0][3] + o3);
                    const uint32_t vAddr = sKV + 5120 + half * 5120 + kvOff;
                    asm volatile("stmatrix.sync.aligned.m8n8.x2.trans.shared.b16 [%0], {%1,%2};" :: "r"(vAddr), "r"(r0), "r"(r1) : "memory");
                    __syncwarp();
                    if (lane < 16) {
                        uint32_t f[4];
                        lds128(f, vAddr);
                        st_async_v4(vAddr + peerBase, f[0], f[1], f[2], f[3], barV + peerBase);
                    }
                }
            }
            named_bar_arrive(6, 384);
            if (s == NSTEPS - 1) break;
            uint32_t wo[16][4];
#pragma unroll
            for (int i = 0; i < 16; i++) lds128(wo[i], wobase + i * 512);
            named_bar_sync(8, 384);
            const uint32_t tag = ((s >> 1) + 1) & 1;
            const uint32_t slotOff = (s & 1) * (64 * 32 * 64);
            {
                float a2[2][2][4];
#pragma unroll
                for (int i = 0; i < 4; i++) { a2[0][0][i] = a2[0][1][i] = a2[1][0][i] = a2[1][1][i] = 0.f; }
                uint32_t b[4][4];
#pragma unroll
                for (int kk = 0; kk < 4; kk++) ldmatrix_x4(b[kk][0], b[kk][1], b[kk][2], b[kk][3], oAddr + kk * 64);
#pragma unroll
                for (int kk = 0; kk < 4; kk++) {
                    mma_nv(a2[0][0], wo[kk * 4 + 0], b[kk][0], b[kk][1]);
                    mma_nv(a2[1][0], wo[kk * 4 + 1], b[kk][0], b[kk][1]);
                    mma_nv(a2[0][1], wo[kk * 4 + 2], b[kk][2], b[kk][3]);
                    mma_nv(a2[1][1], wo[kk * 4 + 3], b[kk][2], b[kk][3]);
                }
#pragma unroll
                for (int mt = 0; mt < 2; mt++) {
                    float c0 = a2[mt][0][0] + a2[mt][1][0], c1 = a2[mt][0][1] + a2[mt][1][1];
                    float c2 = a2[mt][0][2] + a2[mt][1][2], c3 = a2[mt][0][3] + a2[mt][1][3];
                    float* d = partW + slotOff + (mt * 2) * (32 * 64);
                    st_relaxed_v2(d, (__float_as_uint(c0) & ~1u) | tag, __float_as_uint(c1));
                    st_relaxed_v2(d + 32 * 64, (__float_as_uint(c2) & ~1u) | tag, __float_as_uint(c3));
                }
            }
            {
                const float* src = partR + slotOff;
                uint4 v0, v1;
                uint32_t n = 0;
                do { v0 = ld_relaxed_v4(src); v1 = ld_relaxed_v4(src + 1024); }
                while (POLL_R && ((((v0.x ^ tag) | (v1.x ^ tag)) | ((v0.z ^ tag) | (v1.z ^ tag))) & 1u) && ++n < (1u << 22));
                float f0 = __uint_as_float(v0.x) + __uint_as_float(v1.x), f1 = __uint_as_float(v0.y) + __uint_as_float(v1.y);
                float f2 = __uint_as_float(v0.z) + __uint_as_float(v1.z), f3 = __uint_as_float(v0.w) + __uint_as_float(v1.w);
                f0 += __shfl_xor_sync(0xffffffff, f0, 16); f1 += __shfl_xor_sync(0xffffffff, f1, 16);
                f2 += __shfl_xor_sync(0xffffffff, f2, 16); f3 += __shfl_xor_sync(0xffffffff, f3, 16);
                if (lane < 16) asm volatile("st.shared.v4.f32 [%0], {%1,%2,%3,%4};" :: "r"(sb + CH_OFF_RED2 + warp * 256 + lane * 16), "f"(f0), "f"(f1), "f"(f2), "f"(f3) : "memory");
                named_bar_sync(7, 256);
                if (warp == 0) {
                    float u[8][2];
                    const uint32_t ra = sb + CH_OFF_RED2 + ((2 * t4) * 8 + g8) * 4;
#pragma unroll
                    for (int w = 0; w < 8; w++) {
                        asm volatile("ld.shared.f32 %0, [%1];" : "=f"(u[w][0]) : "r"(ra + w * 256) : "memory");
                        asm volatile("ld.shared.f32 %0, [%1];" : "=f"(u[w][1]) : "r"(ra + w * 256 + 32) : "memory");
                    }
                    float a0 = ((u[0][0] + u[1][0]) + (u[2][0] + u[3][0])) + ((u[4][0] + u[5][0]) + (u[6][0] + u[7][0]));
                    float a1 = ((u[0][1] + u[1][1]) + (u[2][1] + u[3][1])) + ((u[4][1] + u[5][1]) + (u[6][1] + u[7][1]));
                    uint32_t m = pack_bf16(a0, a1);
                    uint32_t m1 = __shfl_down_sync(0xffffffff, m, 1), m2 = __shfl_down_sync(0xffffffff, m, 2), m3 = __shfl_down_sync(0xffffffff, m, 3);
                    if (t4 == 0) {
                        if (m == 0u) m = 0x8000u;
                        st_relaxed_v4(memOut + s * 512, m, m1, m2, m3);
                    }
                }
            }
        }
    } else {
        reg_dealloc<88>();
        const int aw = warp - 8;
        const uint32_t peerBase = mapa_u32(sb, peer) - sb;
        const float sm_scale = 0.08838834764831845f * 1.4426950408889634f;
        const int kc64 = 64 + head * 2 + half, vc64 = 128 + head * 2;
        auto issue_kv = [&](int s) {
            if ((s & 3) == 0) {
                uint32_t n = 0;
                while (ld_acquire_u32(p.flags + (s >> 2)) < p.flag_target) { if (++n > (1u << 22)) break; }
                fence_proxy_async_all();
            }
            int st = s & (CH_NKV - 1);
            uint32_t base = sb + CH_OFF_KV + st * CH_KV_BYTES;
            mbar_expect_tx(barKV + 8 * st, 12288);
            tma_load_3d(base + 1024, &p.tmKV, 0, s * 32, kc64, barKV + 8 * st);
            tma_load_3d(base + 5120 + 1024, &p.tmKV, 0, s * 32, vc64, barKV + 8 * st);
            tma_load_3d(base + 10240 + 1024, &p.tmKV, 0, s * 32, vc64 + 1, barKV + 8 * st);
        };
        if (aw == 3 && lane == 0) { for (int s = 0; s < CH_NKV - 1; s++) issue_kv(s); }
        const uint32_t kOff0 = lr * 128 + ((lm ^ lr) << 4), kOff1 = lr * 128 + (((4 + lm) ^ lr) << 4);
        const uint32_t qAddr = (lm & 1) ? (sb + CH_OFF_ZERO) : (sb + CH_OFF_Q + lr * CH_Q_STRIDE + (lm >> 1) * 16);
        const uint32_t qStep = (lm & 1) ? 0u : 32u;
        const uint32_t vRow = ((lm >> 1) * 8 + lr) * 128;
        const uint32_t vOff0 = 5120 + (aw >> 1) * 5120 + vRow + ((((aw & 1) * 4 + (lm & 1)) ^ lr) << 4);
        const uint32_t vOff1 = 5120 + (aw >> 1) * 5120 + vRow + ((((aw & 1) * 4 + 2 + (lm & 1)) ^ lr) << 4);
        const uint32_t padAdj = (lm >> 1) ? 2048u : 0u;
        const uint32_t scAddr = sb + CH_OFF_SC + lane * 8;
        const uint32_t oDst = sb + CH_OFF_O + lr * CH_O_STRIDE + (aw * 32 + lm * 8) * 2;
        const int si = tid - 256, sw = si >> 6, stok = (si >> 3) & 7, scn = si & 7;
        const uint32_t kvmOff = (sw == 0 ? 0u : 5120u + half * 5120u) + stok * 128 + ((scn ^ stok) << 4);
        bf16* kvmDst = p.kvmem + (size_t)stok * 8192 + sw * 4096 + head * 128 + half * 64 + scn * 8;
        const bool leader = (tid == 256);
        for (int s = 0; s < NSTEPS; s++) {
            const uint32_t par = s & 1;
            const int st = s & (CH_NKV - 1);
            const uint32_t sKV = sb + CH_OFF_KV + st * CH_KV_BYTES;
            mbar_wait(barKV + 8 * st, (s / CH_NKV) & 1);
            uint32_t kb[2][4][4], va[3][2][4];
#pragma unroll
            for (int n = 0; n < 4; n++) {
                ldmatrix_x4(kb[0][n][0], kb[0][n][1], kb[0][n][2], kb[0][n][3], sKV + (n + 1) * 1024 + kOff0);
                ldmatrix_x4(kb[1][n][0], kb[1][n][1], kb[1][n][2], kb[1][n][3], sKV + (n + 1) * 1024 + kOff1);
            }
            named_bar_sync(5, 384);
            float sc[5][4];
#pragma unroll
            for (int n = 0; n < 5; n++) { sc[n][0] = sc[n][1] = sc[n][2] = sc[n][3] = 0.f; }
            {
                uint32_t a[4][4], km[2][4];
#pragma unroll
                for (int k = 0; k < 4; k++) ldmatrix_x4(a[k][0], a[k][1], a[k][2], a[k][3], qAddr + k * qStep);
                ldmatrix_x4(km[0][0], km[0][1], km[0][2], km[0][3], sKV + kOff0);
                ldmatrix_x4(km[1][0], km[1][1], km[1][2], km[1][3], sKV + kOff1);
#pragma unroll
                for (int kp = 0; kp < 2; kp++) {
#pragma unroll
                    for (int n = 0; n < 4; n++) mma_nv(sc[n + 1], a[kp * 2], kb[kp][n][0], kb[kp][n][1]);
#pragma unroll
                    for (int n = 0; n < 4; n++) mma_nv(sc[n + 1], a[kp * 2 + 1], kb[kp][n][2], kb[kp][n][3]);
                }
                mma_nv(sc[0], a[0], km[0][0], km[0][1]);
                mma_nv(sc[0], a[1], km[0][2], km[0][3]);
                mma_nv(sc[0], a[2], km[1][0], km[1][1]);
                mma_nv(sc[0], a[3], km[1][2], km[1][3]);
            }
            if (aw == 0) {
#pragma unroll
                for (int n = 0; n < 5; n++) st_async_v2(scAddr + peerBase + n * 256, __float_as_uint(sc[n][0]), __float_as_uint(sc[n][1]), barSc + peerBase);
            }
#pragma unroll
            for (int ks = 1; ks < 3; ks++) {
                const uint32_t adj = ks == 2 ? padAdj : 0u;
                ldmatrix_x4_t(va[ks][0][0], va[ks][0][1], va[ks][0][2], va[ks][0][3], sKV + ks * 2048 + vOff0 - adj);
                ldmatrix_x4_t(va[ks][1][0], va[ks][1][1], va[ks][1][2], va[ks][1][3], sKV + ks * 2048 + vOff1 - adj);
            }
            uint4 kvm;
            if (sw == 0) asm volatile("ld.shared.v4.u32 {%0,%1,%2,%3}, [%4];" : "=r"(kvm.x), "=r"(kvm.y), "=r"(kvm.z), "=r"(kvm.w) : "r"(sKV + kvmOff) : "memory");
            mbar_wait(barSc, par);
            float pp[5][2];
#pragma unroll
            for (int n = 0; n < 5; n++)
                asm volatile("ld.shared.v2.f32 {%0,%1}, [%2];" : "=f"(pp[n][0]), "=f"(pp[n][1]) : "r"(scAddr + n * 256) : "memory");
            if (leader) mbar_expect_tx(barSc, 1280);
#pragma unroll
            for (int n = 0; n < 5; n++) { sc[n][0] += pp[n][0]; sc[n][1] += pp[n][1]; }
            float mx = fmaxf(fmaxf(fmaxf(sc[0][0], sc[0][1]), fmaxf(sc[1][0], sc[1][1])), fmaxf(fmaxf(sc[2][0], sc[2][1]), fmaxf(sc[3][0], sc[3][1])));
            mx = fmaxf(mx, fmaxf(sc[4][0], sc[4][1]));
            mx = fmaxf(mx, __shfl_xor_sync(0xffffffff, mx, 1));
            mx = fmaxf(mx, __shfl_xor_sync(0xffffffff, mx, 2));
            const float mb = mx * sm_scale;
            uint32_t pb[5];
            float e[5][2];
#pragma unroll
            for (int n = 0; n < 5; n++) {
                e[n][0] = ex2_approx(fmaf(sc[n][0], sm_scale, -mb));
                e[n][1] = ex2_approx(fmaf(sc[n][1], sm_scale, -mb));
                pb[n] = pack_bf16(e[n][0], e[n][1]);
            }
            float oc[2][4];
#pragma unroll
            for (int i = 0; i < 4; i++) { oc[0][i] = oc[1][i] = 0.f; }
            mma_nv(oc[0], va[1][0], pb[2], pb[3]);
            mma_nv(oc[1], va[1][1], pb[2], pb[3]);
            mma_nv(oc[0], va[2][0], pb[4], 0u);
            mma_nv(oc[1], va[2][1], pb[4], 0u);
            float sum = ((e[0][0] + e[0][1]) + (e[1][0] + e[1][1])) + ((e[2][0] + e[2][1]) + (e[3][0] + e[3][1])) + (e[4][0] + e[4][1]);
            sum += __shfl_xor_sync(0xffffffff, sum, 1);
            sum += __shfl_xor_sync(0xffffffff, sum, 2);
            const float inv = __fdividef(1.0f, sum);
            const float i0 = __shfl_sync(0xffffffff, inv, t4 * 8), i1 = __shfl_sync(0xffffffff, inv, t4 * 8 + 4);
            named_bar_sync(6, 384);
            mbar_wait(barV, par);
            ldmatrix_x4_t(va[0][0][0], va[0][0][1], va[0][0][2], va[0][0][3], sKV + vOff0);
            ldmatrix_x4_t(va[0][1][0], va[0][1][1], va[0][1][2], va[0][1][3], sKV + vOff1);
            if (leader) mbar_expect_tx(barV, 1024);
            if (sw == 1) asm volatile("ld.shared.v4.u32 {%0,%1,%2,%3}, [%4];" : "=r"(kvm.x), "=r"(kvm.y), "=r"(kvm.z), "=r"(kvm.w) : "r"(sKV + kvmOff) : "memory");
            mma_nv(oc[0], va[0][0], pb[0], pb[1]);
            mma_nv(oc[1], va[0][1], pb[0], pb[1]);
            stmatrix_x4_t(oDst, pack_bf16(oc[0][0] * i0, oc[0][1] * i1), pack_bf16(oc[0][2] * i0, oc[0][3] * i1),
                          pack_bf16(oc[1][0] * i0, oc[1][1] * i1), pack_bf16(oc[1][2] * i0, oc[1][3] * i1));
            if (s < NSTEPS - 1) named_bar_arrive(8, 384);
            *reinterpret_cast<uint4*>(kvmDst + (size_t)s * 65536) = kvm;
            if (p.seg_flags) { __syncwarp(); if (lane == 0) { __threadfence(); atomicAdd(p.seg_flags + s, 1u); } }
            if (aw == 3 && lane == 0 && s + CH_NKV - 1 < NSTEPS) issue_kv(s + CH_NKV - 1);
        }
    }
    __syncthreads();
    cluster_sync_all();
}

struct AttnAParams {
    CUtensorMap tmKV;
    const bf16* qkv;
    bf16* o;
};
constexpr int AA_KT = 256;
constexpr int AA_NST = 3;
constexpr int AA_SMEM = AA_NST * 2 * AA_KT * 32 + 64;

__device__ __forceinline__ float ex2a(float x) { float y; asm("ex2.approx.ftz.f32 %0, %1;" : "=f"(y) : "f"(x)); return y; }
__device__ __forceinline__ void mma_f(float* c, const uint32_t* a, uint32_t b0, uint32_t b1) {
    asm("mma.sync.aligned.m16n8k16.row.col.f32.bf16.bf16.f32 {%0,%1,%2,%3}, {%4,%5,%6,%7}, {%8,%9}, {%0,%1,%2,%3};"
        : "+f"(c[0]), "+f"(c[1]), "+f"(c[2]), "+f"(c[3]) : "r"(a[0]), "r"(a[1]), "r"(a[2]), "r"(a[3]), "r"(b0), "r"(b1));
}

__global__ void __launch_bounds__(256, 2) attn_a_kernel(const __grid_constant__ AttnAParams p) {
    extern __shared__ __align__(1024) unsigned char smem[];
    const uint32_t sb = smem_u32(smem);
    const uint32_t bars = sb + AA_NST * 2 * AA_KT * 32;
    const int tid = threadIdx.x, lane = tid & 31, warp = tid >> 5;
    const int head = blockIdx.x >> 3, qt = blockIdx.x & 7;
    const int t4 = lane & 3, g8 = lane >> 2;
    constexpr int NT = 2048 / AA_KT;

    if (tid == 0) {
        for (int i = 0; i < AA_NST; i++) { mbar_init(bars + 8 * i, 1); mbar_init(bars + 8 * (AA_NST + i), 8); }
        fence_mbar_init();
    }
    __syncthreads();
    auto issue = [&](int t) {
        int st = t % AA_NST;
        uint32_t dst = sb + st * (2 * AA_KT * 32);
        mbar_expect_tx(bars + 8 * st, 2 * AA_KT * 32);
        tma_load_2d(dst, &p.tmKV, 512 + head * 16, t * AA_KT, bars + 8 * st);
        tma_load_2d(dst + AA_KT * 32, &p.tmKV, 1024 + head * 16, t * AA_KT, bars + 8 * st);
    };
    if (tid == 0) { for (int t = 0; t < AA_NST; t++) issue(t); }

    uint32_t qa[2][4];
    const int row0 = qt * 256 + warp * 32;
#pragma unroll
    for (int m = 0; m < 2; m++) {
        const bf16* q = p.qkv + (size_t)(row0 + m * 16 + g8) * 1536 + head * 16 + t4 * 2;
        qa[m][0] = *reinterpret_cast<const uint32_t*>(q);
        qa[m][1] = *reinterpret_cast<const uint32_t*>(q + 8 * 1536);
        qa[m][2] = *reinterpret_cast<const uint32_t*>(q + 8);
        qa[m][3] = *reinterpret_cast<const uint32_t*>(q + 8 * 1536 + 8);
    }
    const float sc = 0.25f * 1.4426950408889634f;
    float mrow[2][2], oacc[2][2][4], lacc[2][4];
#pragma unroll
    for (int m = 0; m < 2; m++) {
        mrow[m][0] = mrow[m][1] = -3.0e38f;
#pragma unroll
        for (int i = 0; i < 4; i++) { oacc[m][0][i] = oacc[m][1][i] = 0.f; lacc[m][i] = 0.f; }
    }
    const uint32_t ones = 0x3F803F80u;
    const int lr = lane & 7, lm = lane >> 3;
    const int krow = (lm >> 1) * 8 + lr, kch = lm & 1;
    const uint32_t koff = krow * 32 + ((kch ^ ((krow >> 2) & 1)) << 4);
    const int vrow = (lm & 1) * 8 + lr, vch = lm >> 1;
    const uint32_t voff = vrow * 32 + ((vch ^ ((vrow >> 2) & 1)) << 4);

    for (int t = 0; t < NT; t++) {
        const int st = t % AA_NST;
        mbar_wait(bars + 8 * st, (t / AA_NST) & 1);
        const uint32_t sK = sb + st * (2 * AA_KT * 32), sV = sK + AA_KT * 32;
#pragma unroll 1
        for (int kb = 0; kb < AA_KT / 64; kb++) {
            float s[2][8][4];
#pragma unroll
            for (int np = 0; np < 4; np++) {
                uint32_t b0, b1, b2, b3;
                ldmatrix_x4(b0, b1, b2, b3, sK + (kb * 64 + np * 16) * 32 + koff);
#pragma unroll
                for (int m = 0; m < 2; m++) {
#pragma unroll
                    for (int i = 0; i < 4; i++) { s[m][np * 2][i] = 0.f; s[m][np * 2 + 1][i] = 0.f; }
                    mma_f(s[m][np * 2], qa[m], b0, b1);
                    mma_f(s[m][np * 2 + 1], qa[m], b2, b3);
                }
            }
            uint32_t pa[2][4][4];
#pragma unroll
            for (int m = 0; m < 2; m++) {
                float mx0 = s[m][0][0], mx1 = s[m][0][2];
#pragma unroll
                for (int n = 0; n < 8; n++) {
                    mx0 = fmaxf(mx0, fmaxf(s[m][n][0], s[m][n][1]));
                    mx1 = fmaxf(mx1, fmaxf(s[m][n][2], s[m][n][3]));
                }
                mx0 = fmaxf(mx0, __shfl_xor_sync(0xffffffff, mx0, 1)); mx0 = fmaxf(mx0, __shfl_xor_sync(0xffffffff, mx0, 2));
                mx1 = fmaxf(mx1, __shfl_xor_sync(0xffffffff, mx1, 1)); mx1 = fmaxf(mx1, __shfl_xor_sync(0xffffffff, mx1, 2));
                const float mn0 = fmaxf(mrow[m][0], mx0), mn1 = fmaxf(mrow[m][1], mx1);
                const float a0 = ex2a((mrow[m][0] - mn0) * sc), a1 = ex2a((mrow[m][1] - mn1) * sc);
                mrow[m][0] = mn0; mrow[m][1] = mn1;
                const float mb0 = mn0 * sc, mb1 = mn1 * sc;
#pragma unroll
                for (int d = 0; d < 2; d++) { oacc[m][d][0] *= a0; oacc[m][d][1] *= a0; oacc[m][d][2] *= a1; oacc[m][d][3] *= a1; }
                lacc[m][0] *= a0; lacc[m][2] *= a1;
#pragma unroll
                for (int n = 0; n < 8; n++) {
                    float p0 = ex2a(fmaf(s[m][n][0], sc, -mb0)), p1 = ex2a(fmaf(s[m][n][1], sc, -mb0));
                    float p2 = ex2a(fmaf(s[m][n][2], sc, -mb1)), p3 = ex2a(fmaf(s[m][n][3], sc, -mb1));
                    pa[m][n >> 1][(n & 1) * 2 + 0] = pack_bf16(p0, p1);
                    pa[m][n >> 1][(n & 1) * 2 + 1] = pack_bf16(p2, p3);
                }
            }
#pragma unroll
            for (int ks = 0; ks < 4; ks++) {
                uint32_t b0, b1, b2, b3;
                ldmatrix_x4_t(b0, b1, b2, b3, sV + (kb * 64 + ks * 16) * 32 + voff);
#pragma unroll
                for (int m = 0; m < 2; m++) {
                    mma_f(oacc[m][0], pa[m][ks], b0, b1);
                    mma_f(oacc[m][1], pa[m][ks], b2, b3);
                    mma_f(lacc[m], pa[m][ks], ones, ones);
                }
            }
        }
        __syncwarp();
        if (lane == 0) mbar_arrive(bars + 8 * (AA_NST + st));
        if (tid == 0 && t + AA_NST < NT) {
            mbar_wait(bars + 8 * (AA_NST + st), (t / AA_NST) & 1);
            issue(t + AA_NST);
        }
    }
#pragma unroll
    for (int m = 0; m < 2; m++) {
        const float i0 = 1.0f / lacc[m][0], i1 = 1.0f / lacc[m][2];
        bf16* o = p.o + (size_t)(row0 + m * 16 + g8) * 512 + head * 16 + t4 * 2;
#pragma unroll
        for (int d = 0; d < 2; d++) {
            *reinterpret_cast<uint32_t*>(o + d * 8) = pack_bf16(oacc[m][d][0] * i0, oacc[m][d][1] * i0);
            *reinterpret_cast<uint32_t*>(o + 8 * 512 + d * 8) = pack_bf16(oacc[m][d][2] * i1, oacc[m][d][3] * i1);
        }
    }
}

struct AttnBParams {
    CUtensorMap tmQKV;
    CUtensorMap tmKVM;
    CUtensorMap tmO;
    const unsigned int* seg_flags;
    unsigned int seg_target;
    unsigned int* tile_flags;
};
constexpr int AB_WARP_BYTES = 28672;
constexpr int AB_SMEM = 4 * AB_WARP_BYTES + 64;

__global__ void __launch_bounds__(128, 2) attn_b_kernel(const __grid_constant__ AttnBParams p) {
    extern __shared__ __align__(1024) unsigned char smem[];
    const int tid = threadIdx.x, lane = tid & 31, warp = tid >> 5;
    const uint32_t sb = smem_u32(smem) + warp * AB_WARP_BYTES;
    const uint32_t bar = smem_u32(smem) + 4 * AB_WARP_BYTES + warp * 8;
    asm volatile("griddepcontrol.launch_dependents;" ::: "memory");
    const int seg = blockIdx.x >> 3, head = (blockIdx.x & 7) * 4 + warp;
    const int t4 = lane & 3, g8 = lane >> 2;
    const uint32_t sQ = sb, sK = sb + 8192, sV = sb + 16384, sKm = sb + 24576, sVm = sb + 26624;
    if (lane == 0) {
        mbar_init(bar, 1);
        fence_mbar_init();
        if (p.seg_flags) {
            uint32_t n = 0;
            while (ld_acquire_u32(p.seg_flags + seg) < p.seg_target) { if (++n > (1u << 24)) break; __nanosleep(200); }
            fence_proxy_async_all();
        }
        mbar_expect_tx(bar, AB_WARP_BYTES);
#pragma unroll
        for (int h = 0; h < 2; h++) {
            tma_load_3d(sQ + h * 4096, &p.tmQKV, 0, seg * 32, head * 2 + h, bar);
            tma_load_3d(sK + h * 4096, &p.tmQKV, 0, seg * 32, 64 + head * 2 + h, bar);
            tma_load_3d(sV + h * 4096, &p.tmQKV, 0, seg * 32, 128 + head * 2 + h, bar);
            tma_load_3d(sKm + h * 1024, &p.tmKVM, 0, seg * 8, head * 2 + h, bar);
            tma_load_3d(sVm + h * 1024, &p.tmKVM, 0, seg * 8, 64 + head * 2 + h, bar);
        }
    }
    __syncwarp();
    mbar_wait(bar, 0);
    const int lr = lane & 7, lm = lane >> 3;
    float s[2][5][4];
#pragma unroll
    for (int m = 0; m < 2; m++)
#pragma unroll
        for (int n = 0; n < 5; n++)
#pragma unroll
            for (int i = 0; i < 4; i++) s[m][n][i] = 0.f;
#pragma unroll
    for (int kp = 0; kp < 4; kp++) {
        const int hb = kp >> 1, c0 = (kp & 1) * 4;
        uint32_t a[2][2][4];
#pragma unroll
        for (int m = 0; m < 2; m++)
#pragma unroll
            for (int ks = 0; ks < 2; ks++) {
                int row = m * 16 + (lm & 1) * 8 + lr, ch = c0 + ks * 2 + (lm >> 1);
                ldmatrix_x4(a[m][ks][0], a[m][ks][1], a[m][ks][2], a[m][ks][3], sQ + hb * 4096 + row * 128 + ((ch ^ (row & 7)) << 4));
            }
#pragma unroll
        for (int n = 0; n < 5; n++) {
            uint32_t b0, b1, b2, b3;
            int ch = c0 + lm;
            if (n == 0) ldmatrix_x4(b0, b1, b2, b3, sKm + hb * 1024 + lr * 128 + ((ch ^ lr) << 4));
            else { int row = (n - 1) * 8 + lr; ldmatrix_x4(b0, b1, b2, b3, sK + hb * 4096 + row * 128 + ((ch ^ (row & 7)) << 4)); }
#pragma unroll
            for (int m = 0; m < 2; m++) { mma_f(s[m][n], a[m][0], b0, b1); mma_f(s[m][n], a[m][1], b2, b3); }
        }
    }
    const float sc = 0.08838834764831845f * 1.4426950408889634f;
    uint32_t pa[2][3][4];
    float inv[2][2];
#pragma unroll
    for (int m = 0; m < 2; m++) {
        const int r0 = m * 16 + g8, r1 = r0 + 8;
        float mx0 = -3.0e38f, mx1 = -3.0e38f;
#pragma unroll
        for (int n = 0; n < 5; n++) {
            if (n > 0) {
                int j = (n - 1) * 8 + t4 * 2;
                if (j > r0) s[m][n][0] = -3.0e38f;
                if (j + 1 > r0) s[m][n][1] = -3.0e38f;
                if (j > r1) s[m][n][2] = -3.0e38f;
                if (j + 1 > r1) s[m][n][3] = -3.0e38f;
            }
            mx0 = fmaxf(mx0, fmaxf(s[m][n][0], s[m][n][1]));
            mx1 = fmaxf(mx1, fmaxf(s[m][n][2], s[m][n][3]));
        }
        mx0 = fmaxf(mx0, __shfl_xor_sync(0xffffffff, mx0, 1)); mx0 = fmaxf(mx0, __shfl_xor_sync(0xffffffff, mx0, 2));
        mx1 = fmaxf(mx1, __shfl_xor_sync(0xffffffff, mx1, 1)); mx1 = fmaxf(mx1, __shfl_xor_sync(0xffffffff, mx1, 2));
        const float mb0 = mx0 * sc, mb1 = mx1 * sc;
        float l0 = 0.f, l1 = 0.f;
#pragma unroll
        for (int n = 0; n < 5; n++) {
            s[m][n][0] = ex2a(fmaf(s[m][n][0], sc, -mb0)); s[m][n][1] = ex2a(fmaf(s[m][n][1], sc, -mb0));
            s[m][n][2] = ex2a(fmaf(s[m][n][2], sc, -mb1)); s[m][n][3] = ex2a(fmaf(s[m][n][3], sc, -mb1));
            l0 += s[m][n][0] + s[m][n][1]; l1 += s[m][n][2] + s[m][n][3];
        }
        l0 += __shfl_xor_sync(0xffffffff, l0, 1); l0 += __shfl_xor_sync(0xffffffff, l0, 2);
        l1 += __shfl_xor_sync(0xffffffff, l1, 1); l1 += __shfl_xor_sync(0xffffffff, l1, 2);
        inv[m][0] = 1.0f / l0; inv[m][1] = 1.0f / l1;
#pragma unroll
        for (int n = 0; n < 5; n++) {
            pa[m][n >> 1][(n & 1) * 2 + 0] = pack_bf16(s[m][n][0] * inv[m][0], s[m][n][1] * inv[m][0]);
            pa[m][n >> 1][(n & 1) * 2 + 1] = pack_bf16(s[m][n][2] * inv[m][1], s[m][n][3] * inv[m][1]);
        }
        pa[m][2][2] = 0u; pa[m][2][3] = 0u;
    }
    __syncwarp();
#pragma unroll
    for (int dq = 0; dq < 4; dq++) {
        float oc[2][4][4];
#pragma unroll
        for (int m = 0; m < 2; m++)
#pragma unroll
            for (int n = 0; n < 4; n++)
#pragma unroll
                for (int i = 0; i < 4; i++) oc[m][n][i] = 0.f;
        const int hb = dq >> 1, c0 = (dq & 1) * 4;
#pragma unroll
        for (int ks = 0; ks < 3; ks++) {
#pragma unroll
            for (int dp = 0; dp < 2; dp++) {
                int key = ks * 16 + (lm & 1) * 8 + lr, ch = c0 + dp * 2 + (lm >> 1);
                uint32_t addr;
                if (key < 8 || key >= 40) addr = sVm + hb * 1024 + lr * 128 + ((ch ^ lr) << 4);
                else { int row = key - 8; addr = sV + hb * 4096 + row * 128 + ((ch ^ (row & 7)) << 4); }
                uint32_t b0, b1, b2, b3;
                ldmatrix_x4_t(b0, b1, b2, b3, addr);
#pragma unroll
                for (int m = 0; m < 2; m++) { mma_f(oc[m][dp * 2], pa[m][ks], b0, b1); mma_f(oc[m][dp * 2 + 1], pa[m][ks], b2, b3); }
            }
        }
#pragma unroll
        for (int m = 0; m < 2; m++)
#pragma unroll
            for (int dp = 0; dp < 2; dp++) {
                int row = m * 16 + (lm & 1) * 8 + lr, ch = c0 + dp * 2 + (lm >> 1);
                stmatrix_x4(sQ + hb * 4096 + row * 128 + ((ch ^ (row & 7)) << 4),
                            pack_bf16(oc[m][dp * 2][0], oc[m][dp * 2][1]), pack_bf16(oc[m][dp * 2][2], oc[m][dp * 2][3]),
                            pack_bf16(oc[m][dp * 2 + 1][0], oc[m][dp * 2 + 1][1]), pack_bf16(oc[m][dp * 2 + 1][2], oc[m][dp * 2 + 1][3]));
            }
    }
    fence_proxy_async_smem();
    __syncwarp();
    if (lane == 0) {
        tma_store_3d(&p.tmO, sQ, 0, seg * 32, head * 2);
        tma_store_3d(&p.tmO, sQ + 4096, 0, seg * 32, head * 2 + 1);
        bulk_commit();
        bulk_wait_all0();
        fence_proxy_async_all();
        __threadfence();
        atomicAdd(p.tile_flags + (seg >> 2), 1u);
    }
}

struct GemmSParams {
    CUtensorMap tmA;
    CUtensorMap tmB;
    CUtensorMap tmC;
    int n_tiles;
    int kblocks_half;
    int c_col64;
    const unsigned int* tile_flags;
    unsigned int tile_target;
};
constexpr int GS_NST = 5;
constexpr int GS_SMEM = GS_NST * 32768 + 32768 + 256;

__global__ void __launch_bounds__(288, 1) gemm_s_kernel(const __grid_constant__ GemmSParams p) {
    extern __shared__ __align__(1024) unsigned char smem[];
    const uint32_t sS = smem_u32(smem);
    const uint32_t sR = sS + GS_NST * 32768;
    const uint32_t bars = sR + 32768;
    const uint32_t barFull = bars, barEmpty = bars + 8 * GS_NST, barRed = bars + 16 * GS_NST;
    const int warp = __shfl_sync(0xffffffff, threadIdx.x >> 5, 0), lane = threadIdx.x & 31;
    const int tile = blockIdx.x >> 1, kh = blockIdx.x & 1;
    const int mt = tile / p.n_tiles, nt = tile % p.n_tiles;
    if (threadIdx.x == 0) {
        for (int i = 0; i < GS_NST; i++) { mbar_init(barFull + 8 * i, 1); mbar_init(barEmpty + 8 * i, 8); }
        mbar_init(barRed, 1);
        fence_mbar_init();
        mbar_expect_tx(barRed, 32768);
    }
    __syncthreads();
    cluster_sync_all();
    if (warp == 8) {
        if (lane == 0) {
            {
                uint32_t n = 0;
                while (ld_acquire_u32(p.tile_flags + mt) < p.tile_target) { if (++n > (1u << 24)) break; __nanosleep(200); }
                fence_proxy_async_all();
            }
            for (int i = 0; i < p.kblocks_half; i++) {
                int slot = i % GS_NST;
                if (i >= GS_NST) mbar_wait(barEmpty + 8 * slot, ((i / GS_NST) - 1) & 1);
                mbar_expect_tx(barFull + 8 * slot, 32768);
                int kb = kh * p.kblocks_half + i;
                tma_load_3d(sS + slot * 32768, &p.tmA, 0, mt * 128, kb, barFull + 8 * slot);
                tma_load_3d(sS + slot * 32768 + 16384, &p.tmB, 0, kb * 64, nt * 2, barFull + 8 * slot);
            }
        }
    } else {
        const int wg = warp >> 2, wq = warp & 3;
        float acc[64];
        int prev = 0;
        for (int i = 0; i < p.kblocks_half; i++) {
            int slot = i % GS_NST;
            mbar_wait(barFull + 8 * slot, (i / GS_NST) & 1);
            wg_fence();
            uint64_t da = make_desc(sS + slot * 32768 + wg * 8192, 16, 1024);
            uint64_t db = make_desc(sS + slot * 32768 + 16384, 8192, 1024);
#pragma unroll
            for (int kk = 0; kk < 4; kk++)
                wgmma_m64n128k16_ss_tb(acc, da + (uint64_t)(kk * 2), db + (uint64_t)(kk * 128), (i | kk) != 0);
            wg_commit();
            if (i > 0) { wg_wait<1>(); if (lane == 0) mbar_arrive(barEmpty + 8 * prev); }
            prev = slot;
        }
        wg_wait<0>();
        const uint32_t peer = kh ^ 1;
        const uint32_t rbuf = mapa_u32(sR, peer), rbar = mapa_u32(barRed, peer);
        const int tw = threadIdx.x;
#pragma unroll
        for (int j = 0; j < 8; j++) {
            float a[4];
#pragma unroll
            for (int i = 0; i < 4; i++) a[i] = kh == 0 ? acc[(8 + j) * 4 + i] : acc[j * 4 + i];
            st_async_v4(rbuf + (j * 256 + tw) * 16, __float_as_uint(a[0]), __float_as_uint(a[1]), __float_as_uint(a[2]), __float_as_uint(a[3]), rbar);
        }
        mbar_wait(barRed, 0);
        named_bar_sync(1, 256);
        const uint32_t stage = sS + wg * 8192;
        const int mrow = wq * 16 + (lane & 7) + ((lane >> 3) & 1) * 8, mcolh = lane >> 4;
#pragma unroll
        for (int c = 0; c < 4; c++) {
            uint32_t r[4];
#pragma unroll
            for (int e = 0; e < 2; e++) {
                int j = c * 2 + e;
                float4 v;
                asm volatile("ld.shared.v4.f32 {%0,%1,%2,%3}, [%4];" : "=f"(v.x), "=f"(v.y), "=f"(v.z), "=f"(v.w) : "r"(sR + (j * 256 + tw) * 16) : "memory");
                float a[4];
#pragma unroll
                for (int i = 0; i < 4; i++) a[i] = kh == 0 ? acc[j * 4 + i] : acc[(8 + j) * 4 + i];
                r[e * 2 + 0] = pack_bf16(a[0] + v.x, a[1] + v.y);
                r[e * 2 + 1] = pack_bf16(a[2] + v.z, a[3] + v.w);
            }
            int chunk = (c * 2 + mcolh) ^ (mrow & 7);
            stmatrix_x4(stage + mrow * 128 + chunk * 16, r[0], r[1], r[2], r[3]);
        }
        fence_proxy_async_smem();
        named_bar_sync(2 + wg, 128);
        if ((threadIdx.x & 127) == 0) {
            tma_store_3d(&p.tmC, stage, 0, mt * 128 + wg * 64, p.c_col64 + nt * 2 + kh);
            bulk_commit();
            bulk_wait_read0();
        }
    }
    __syncthreads();
    cluster_sync_all();
}

typedef CUresult (*PFN_encodeTiled)(CUtensorMap*, CUtensorMapDataType, cuuint32_t, void*, const cuuint64_t*, const cuuint64_t*,
                                    const cuuint32_t*, const cuuint32_t*, CUtensorMapInterleave, CUtensorMapSwizzle,
                                    CUtensorMapL2promotion, CUtensorMapFloatOOBfill);
static PFN_encodeTiled g_encode = nullptr;
static void init_encode() {
    if (g_encode) return;
    void* fn = nullptr;
    cudaDriverEntryPointQueryResult st;
    cudaGetDriverEntryPoint("cuTensorMapEncodeTiled", &fn, cudaEnableDefault, &st);
    g_encode = (PFN_encodeTiled)fn;
}
static CUtensorMap make_tmap_3d64(const void* ptr, uint64_t rows, uint64_t cols, uint64_t ld, uint32_t box_rows, uint32_t box_c64) {
    CUtensorMap tm;
    cuuint64_t dims[3] = {64, rows, cols / 64};
    cuuint64_t strides[2] = {ld * 2, 128};
    cuuint32_t box[3] = {64, box_rows, box_c64};
    cuuint32_t es[3] = {1, 1, 1};
    g_encode(&tm, CU_TENSOR_MAP_DATA_TYPE_BFLOAT16, 3, (void*)ptr, dims, strides, box, es, CU_TENSOR_MAP_INTERLEAVE_NONE,
             CU_TENSOR_MAP_SWIZZLE_128B, CU_TENSOR_MAP_L2_PROMOTION_L2_128B, CU_TENSOR_MAP_FLOAT_OOB_FILL_NONE);
    return tm;
}

__device__ __align__(1024) bf16 g_qkvA[2048 * 1536];
__device__ __align__(1024) bf16 g_oA[2048 * 512];
__device__ __align__(1024) bf16 g_qkvB[2048 * 12288];
__device__ __align__(1024) bf16 g_kvmem[64 * 8 * 8192];
__device__ __align__(1024) bf16 g_oB[2048 * 4096];
__device__ __align__(1024) float g_part[2 * 64 * 32 * 64];
__device__ __align__(1024) uint4 g_membuf[64 * 512];
__device__ __align__(128) unsigned int g_flags[192];

__global__ void cleanup_kernel() {
    const int i = blockIdx.x * blockDim.x + threadIdx.x;
    const int n = gridDim.x * blockDim.x;
    uint4 z = make_uint4(0, 0, 0, 0);
    for (int k = i; k < 2 * 64 * 32 * 16; k += n) reinterpret_cast<uint4*>(g_part)[k] = z;
    for (int k = i; k < 64 * 512; k += n) g_membuf[k] = z;
    if (i < 192) g_flags[i] = 0u;
}

template <typename T> static T* sym_addr(T& sym) { void* p = nullptr; cudaGetSymbolAddress(&p, sym); return (T*)p; }

extern "C" void kernel_launch(void* const* d_in, const int* in_sizes, int n_in, void* d_out, int out_size) {
    const bf16* A_x = (const bf16*)d_in[0];
    const bf16* A_wqkv = (const bf16*)d_in[1];
    const bf16* A_wo = (const bf16*)d_in[2];
    const bf16* B_x = (const bf16*)d_in[3];
    const bf16* B_mem0 = (const bf16*)d_in[4];
    const bf16* B_Wq = (const bf16*)d_in[5];
    const bf16* B_Wk = (const bf16*)d_in[6];
    const bf16* B_Wv = (const bf16*)d_in[7];
    const bf16* B_Wo = (const bf16*)d_in[8];
    bf16* out = (bf16*)d_out;

    static bool inited = false;
    static cudaStream_t s1;
    static cudaEvent_t e_kv, e_s1;
    if (!inited) {
        init_encode();
        cudaFuncSetAttribute(gemm_w_kernel, cudaFuncAttributeMaxDynamicSharedMemorySize, GW_SMEM);
        cudaFuncSetAttribute(gemm_s_kernel, cudaFuncAttributeMaxDynamicSharedMemorySize, GS_SMEM);
        cudaFuncSetAttribute(chain_kernel, cudaFuncAttributeMaxDynamicSharedMemorySize, CH_SMEM);
        cudaFuncSetAttribute(attn_a_kernel, cudaFuncAttributeMaxDynamicSharedMemorySize, AA_SMEM);
        cudaFuncSetAttribute(attn_b_kernel, cudaFuncAttributeMaxDynamicSharedMemorySize, AB_SMEM);
        cudaStreamCreateWithFlags(&s1, cudaStreamNonBlocking);
        cudaEventCreateWithFlags(&e_kv, cudaEventDisableTiming);
        cudaEventCreateWithFlags(&e_s1, cudaEventDisableTiming);
        inited = true;
    }
    void *qkvA, *oA, *qkvB, *kvmem, *oB, *part, *membuf, *flags;
    cudaGetSymbolAddress(&qkvA, g_qkvA); cudaGetSymbolAddress(&oA, g_oA); cudaGetSymbolAddress(&qkvB, g_qkvB);
    cudaGetSymbolAddress(&kvmem, g_kvmem); cudaGetSymbolAddress(&oB, g_oB); cudaGetSymbolAddress(&part, g_part);
    cudaGetSymbolAddress(&membuf, g_membuf); cudaGetSymbolAddress(&flags, g_flags);
    cudaStream_t s0 = cudaStreamPerThread;

    GemmWParams pkv;
    pkv.tmA = make_tmap_3d64(B_x, 2048, 512, 512, 128, 1);
    pkv.tmB[0] = make_tmap_3d64(B_Wk, 512, 4096, 4096, 64, 2);
    pkv.tmB[1] = make_tmap_3d64(B_Wv, 512, 4096, 4096, 64, 2);
    pkv.tmB[2] = make_tmap_3d64(B_Wq, 512, 4096, 4096, 64, 2);
    pkv.tmC = make_tmap_3d64(qkvB, 2048, 12288, 12288, 128, 1);
    pkv.ntiles_per_mat = 32; pkv.c_col64[0] = 64; pkv.c_col64[1] = 128; pkv.c_col64[2] = 0;
    pkv.m_splits = 1; pkv.mtiles_per_cta = 16; pkv.flag_mats = 2; pkv.flags = (unsigned int*)flags;
    gemm_w_kernel<<<64, 384, GW_SMEM, s0>>>(pkv);
    cudaEventRecord(e_kv, s0);

    ChainParams pc;
    pc.tmW[0] = make_tmap_3d64(B_Wq, 512, 4096, 4096, 256, 1);
    pc.tmW[1] = make_tmap_3d64(B_Wk, 512, 4096, 4096, 256, 1);
    pc.tmW[2] = make_tmap_3d64(B_Wv, 512, 4096, 4096, 256, 1);
    pc.tmWo = make_tmap_3d64(B_Wo, 4096, 512, 512, 128, 1);
    pc.tmKV = make_tmap_3d64(qkvB, 2048, 12288, 12288, 32, 1);
    pc.mem0 = B_mem0; pc.kvmem = (bf16*)kvmem; pc.part = (float*)part; pc.membuf = (uint4*)membuf;
    pc.flags = (const unsigned int*)flags; pc.flag_target = 128; pc.dbg = nullptr; pc.seg_flags = (unsigned int*)flags + 64;
    {
        cudaLaunchConfig_t cfg = {};
        cfg.gridDim = dim3(64); cfg.blockDim = dim3(384); cfg.dynamicSmemBytes = CH_SMEM; cfg.stream = s0;
        cudaLaunchAttribute at[2];
        at[0].id = cudaLaunchAttributeClusterDimension; at[0].val.clusterDim.x = 2; at[0].val.clusterDim.y = 1; at[0].val.clusterDim.z = 1;
        at[1].id = cudaLaunchAttributeProgrammaticStreamSerialization; at[1].val.programmaticStreamSerializationAllowed = 1;
        cfg.attrs = at; cfg.numAttrs = 2;
        cudaLaunchKernelEx(&cfg, chain_kernel, pc);
    }

    cudaStreamWaitEvent(s1, e_kv, 0);
    GemmWParams pq = pkv;
    pq.tmB[0] = pkv.tmB[2]; pq.c_col64[0] = 0; pq.m_splits = 2; pq.mtiles_per_cta = 8; pq.flag_mats = 0; pq.flags = nullptr;
    gemm_w_kernel<<<64, 384, GW_SMEM, s1>>>(pq);

    GemmWParams p1;
    p1.tmA = make_tmap_3d64(A_x, 2048, 512, 512, 128, 1);
    p1.tmB[0] = make_tmap_3d64(A_wqkv, 512, 1536, 1536, 64, 2); p1.tmB[1] = p1.tmB[0]; p1.tmB[2] = p1.tmB[0];
    p1.tmC = make_tmap_3d64(qkvA, 2048, 1536, 1536, 128, 1);
    p1.ntiles_per_mat = 12; p1.c_col64[0] = p1.c_col64[1] = p1.c_col64[2] = 0;
    p1.m_splits = 4; p1.mtiles_per_cta = 4; p1.flag_mats = 0; p1.flags = nullptr;
    gemm_w_kernel<<<48, 384, GW_SMEM, s1>>>(p1);

    AttnAParams pa;
    {
        cuuint64_t dims[2] = {1536, 2048}; cuuint64_t strides[1] = {3072}; cuuint32_t box[2] = {16, AA_KT}; cuuint32_t es[2] = {1, 1};
        g_encode(&pa.tmKV, CU_TENSOR_MAP_DATA_TYPE_BFLOAT16, 2, qkvA, dims, strides, box, es, CU_TENSOR_MAP_INTERLEAVE_NONE,
                 CU_TENSOR_MAP_SWIZZLE_32B, CU_TENSOR_MAP_L2_PROMOTION_L2_128B, CU_TENSOR_MAP_FLOAT_OOB_FILL_NONE);
    }
    pa.qkv = (const bf16*)qkvA; pa.o = (bf16*)oA;
    attn_a_kernel<<<256, 256, AA_SMEM, s1>>>(pa);

    GemmWParams p2;
    p2.tmA = make_tmap_3d64(oA, 2048, 512, 512, 128, 1);
    p2.tmB[0] = make_tmap_3d64(A_wo, 512, 512, 512, 64, 2); p2.tmB[1] = p2.tmB[0]; p2.tmB[2] = p2.tmB[0];
    p2.tmC = make_tmap_3d64(out, 2048, 1024, 1024, 128, 1);
    p2.ntiles_per_mat = 4; p2.c_col64[0] = p2.c_col64[1] = p2.c_col64[2] = 0;
    p2.m_splits = 16; p2.mtiles_per_cta = 1; p2.flag_mats = 0; p2.flags = nullptr;
    gemm_w_kernel<<<64, 384, GW_SMEM, s1>>>(p2);

    AttnBParams pb;
    pb.tmQKV = make_tmap_3d64(qkvB, 2048, 12288, 12288, 32, 1);
    pb.tmKVM = make_tmap_3d64(kvmem, 512, 8192, 8192, 8, 1);
    pb.tmO = make_tmap_3d64(oB, 2048, 4096, 4096, 32, 1);
    pb.seg_flags = (const unsigned int*)flags + 64; pb.seg_target = 256; pb.tile_flags = (unsigned int*)flags + 128;
    attn_b_kernel<<<512, 128, AB_SMEM, s1>>>(pb);

    GemmSParams p4;
    p4.tmA = make_tmap_3d64(oB, 2048, 4096, 4096, 128, 1);
    p4.tmB = make_tmap_3d64(B_Wo, 4096, 512, 512, 64, 2);
    p4.tmC = make_tmap_3d64(out, 2048, 1024, 1024, 64, 1);
    p4.n_tiles = 4; p4.kblocks_half = 32; p4.c_col64 = 8;
    p4.tile_flags = (const unsigned int*)flags + 128; p4.tile_target = 128;
    {
        cudaLaunchConfig_t cfg = {};
        cfg.gridDim = dim3(128); cfg.blockDim = dim3(288); cfg.dynamicSmemBytes = GS_SMEM; cfg.stream = s1;
        cudaLaunchAttribute at[2];
        at[0].id = cudaLaunchAttributeClusterDimension; at[0].val.clusterDim.x = 2; at[0].val.clusterDim.y = 1; at[0].val.clusterDim.z = 1;
        at[1].id = cudaLaunchAttributeProgrammaticStreamSerialization; at[1].val.programmaticStreamSerializationAllowed = 1;
        cfg.attrs = at; cfg.numAttrs = 2;
        cudaLaunchKernelEx(&cfg, gemm_s_kernel, p4);
    }
    cudaEventRecord(e_s1, s1);
    cudaStreamWaitEvent(s0, e_s1, 0);
    cleanup_kernel<<<64, 256, 0, s0>>>();
}
```

```cpp
#include <cuda_runtime.h>
#include <cuda_bf16.h>
#include <cuda.h>
#include <stdint.h>

typedef __nv_bfloat16 bf16;

__device__ __forceinline__ uint32_t smem_u32(const void* p) { return (uint32_t)__cvta_generic_to_shared(p); }
__device__ __forceinline__ void mbar_init(uint32_t bar, uint32_t cnt) {
    asm volatile("mbarrier.init.shared::cta.b64 [%0], %1;" :: "r"(bar), "r"(cnt) : "memory");
}
__device__ __forceinline__ void mbar_expect_tx(uint32_t bar, uint32_t bytes) {
    asm volatile("mbarrier.arrive.expect_tx.shared::cta.b64 _, [%0], %1;" :: "r"(bar), "r"(bytes) : "memory");
}
__device__ __forceinline__ void mbar_arrive(uint32_t bar) {
    asm volatile("mbarrier.arrive.shared::cta.b64 _, [%0];" :: "r"(bar) : "memory");
}
__device__ __forceinline__ bool mbar_try_wait(uint32_t bar, uint32_t parity) {
    uint32_t ok;
    asm volatile("{\n.reg .pred p;\nmbarrier.try_wait.parity.shared::cta.b64 p, [%1], %2;\nselp.u32 %0, 1, 0, p;\n}"
                 : "=r"(ok) : "r"(bar), "r"(parity) : "memory");
    return ok != 0;
}
__device__ __forceinline__ void mbar_wait(uint32_t bar, uint32_t parity) {
    uint32_t n = 0;
    while (!mbar_try_wait(bar, parity)) { if (++n > (1u << 20)) break; }
}
__device__ __forceinline__ void fence_proxy_async_smem() { asm volatile("fence.proxy.async.shared::cta;" ::: "memory"); }
__device__ __forceinline__ void fence_proxy_async_all() { asm volatile("fence.proxy.async;" ::: "memory"); }
__device__ __forceinline__ void fence_mbar_init() { asm volatile("fence.mbarrier_init.release.cluster;" ::: "memory"); }

__device__ __forceinline__ void tma_load_3d(uint32_t dst, const CUtensorMap* tm, int c0, int c1, int c2, uint32_t bar) {
    asm volatile("cp.async.bulk.tensor.3d.shared::cluster.global.mbarrier::complete_tx::bytes [%0], [%1, {%3, %4, %5}], [%2];"
                 :: "r"(dst), "l"(tm), "r"(bar), "r"(c0), "r"(c1), "r"(c2) : "memory");
}
__device__ __forceinline__ void tma_load_2d(uint32_t dst, const CUtensorMap* tm, int c0, int c1, uint32_t bar) {
    asm volatile("cp.async.bulk.tensor.2d.shared::cluster.global.mbarrier::complete_tx::bytes [%0], [%1, {%3, %4}], [%2];"
                 :: "r"(dst), "l"(tm), "r"(bar), "r"(c0), "r"(c1) : "memory");
}
__device__ __forceinline__ void tma_store_3d(const CUtensorMap* tm, uint32_t src, int c0, int c1, int c2) {
    asm volatile("cp.async.bulk.tensor.3d.global.shared::cta.bulk_group [%0, {%2, %3, %4}], [%1];"
                 :: "l"(tm), "r"(src), "r"(c0), "r"(c1), "r"(c2) : "memory");
}
__device__ __forceinline__ void bulk_commit() { asm volatile("cp.async.bulk.commit_group;" ::: "memory"); }
__device__ __forceinline__ void bulk_wait_read0() { asm volatile("cp.async.bulk.wait_group.read 0;" ::: "memory"); }
__device__ __forceinline__ void bulk_wait_all0() { asm volatile("cp.async.bulk.wait_group 0;" ::: "memory"); }
__device__ __forceinline__ void prefetch_tmap(const CUtensorMap* tm) {
    asm volatile("prefetch.tensormap [%0];" :: "l"(tm) : "memory");
}

__device__ __forceinline__ void wg_fence() { asm volatile("wgmma.fence.sync.aligned;" ::: "memory"); }
__device__ __forceinline__ void wg_commit() { asm volatile("wgmma.commit_group.sync.aligned;" ::: "memory"); }
template <int N> __device__ __forceinline__ void wg_wait() { asm volatile("wgmma.wait_group.sync.aligned %0;" :: "n"(N) : "memory"); }

__device__ __forceinline__ void named_bar_sync(int id, int nthreads) {
    asm volatile("bar.sync %0, %1;" :: "r"(id), "r"(nthreads) : "memory");
}
__device__ __forceinline__ void named_bar_arrive(int id, int nthreads) {
    asm volatile("bar.arrive %0, %1;" :: "r"(id), "r"(nthreads) : "memory");
}

__device__ __forceinline__ uint64_t make_desc(uint32_t saddr, uint32_t lbo_bytes, uint32_t sbo_bytes) {
    return (uint64_t)((saddr & 0x3FFFF) >> 4) | ((uint64_t)(lbo_bytes >> 4) << 16) | ((uint64_t)(sbo_bytes >> 4) << 32) | ((uint64_t)1 << 62);
}

__device__ __forceinline__ uint32_t pack_bf16(float lo, float hi) {
    uint32_t r;
    asm("cvt.rn.bf16x2.f32 %0, %1, %2;" : "=r"(r) : "f"(hi), "f"(lo));
    return r;
}
__device__ __forceinline__ void stmatrix_x4(uint32_t addr, uint32_t r0, uint32_t r1, uint32_t r2, uint32_t r3) {
    asm volatile("stmatrix.sync.aligned.m8n8.x4.shared.b16 [%0], {%1,%2,%3,%4};" :: "r"(addr), "r"(r0), "r"(r1), "r"(r2), "r"(r3) : "memory");
}
__device__ __forceinline__ void ldmatrix_x4(uint32_t& r0, uint32_t& r1, uint32_t& r2, uint32_t& r3, uint32_t addr) {
    asm volatile("ldmatrix.sync.aligned.m8n8.x4.shared.b16 {%0,%1,%2,%3}, [%4];" : "=r"(r0), "=r"(r1), "=r"(r2), "=r"(r3) : "r"(addr) : "memory");
}
__device__ __forceinline__ void ldmatrix_x4_t(uint32_t& r0, uint32_t& r1, uint32_t& r2, uint32_t& r3, uint32_t addr) {
    asm volatile("ldmatrix.sync.aligned.m8n8.x4.trans.shared.b16 {%0,%1,%2,%3}, [%4];" : "=r"(r0), "=r"(r1), "=r"(r2), "=r"(r3) : "r"(addr) : "memory");
}
__device__ __forceinline__ void ldmatrix_x2(uint32_t& r0, uint32_t& r1, uint32_t addr) {
    asm volatile("ldmatrix.sync.aligned.m8n8.x2.shared.b16 {%0,%1}, [%2];" : "=r"(r0), "=r"(r1) : "r"(addr) : "memory");
}
__device__ __forceinline__ void ldmatrix_x2_t(uint32_t& r0, uint32_t& r1, uint32_t addr) {
    asm volatile("ldmatrix.sync.aligned.m8n8.x2.trans.shared.b16 {%0,%1}, [%2];" : "=r"(r0), "=r"(r1) : "r"(addr) : "memory");
}
__device__ __forceinline__ void mma16816(float* c, const uint32_t* a, uint32_t b0, uint32_t b1) {
    asm volatile("mma.sync.aligned.m16n8k16.row.col.f32.bf16.bf16.f32 {%0,%1,%2,%3}, {%4,%5,%6,%7}, {%8,%9}, {%0,%1,%2,%3};"
                 : "+f"(c[0]), "+f"(c[1]), "+f"(c[2]), "+f"(c[3]) : "r"(a[0]), "r"(a[1]), "r"(a[2]), "r"(a[3]), "r"(b0), "r"(b1));
}

__device__ __forceinline__ void wgmma_m64n128k16_ss_tb(float* d, uint64_t da, uint64_t db, int scale_d) {
    asm volatile(
        "{\n.reg .pred p;\nsetp.ne.b32 p, %66, 0;\n"
        "wgmma.mma_async.sync.aligned.m64n128k16.f32.bf16.bf16 "
        "{%0,%1,%2,%3,%4,%5,%6,%7,%8,%9,%10,%11,%12,%13,%14,%15,"
        "%16,%17,%18,%19,%20,%21,%22,%23,%24,%25,%26,%27,%28,%29,%30,%31,"
        "%32,%33,%34,%35,%36,%37,%38,%39,%40,%41,%42,%43,%44,%45,%46,%47,"
        "%48,%49,%50,%51,%52,%53,%54,%55,%56,%57,%58,%59,%60,%61,%62,%63},"
        " %64, %65, p, 1, 1, 0, 1;\n}\n"
        : "+f"(d[0]), "+f"(d[1]), "+f"(d[2]), "+f"(d[3]), "+f"(d[4]), "+f"(d[5]), "+f"(d[6]), "+f"(d[7]),
          "+f"(d[8]), "+f"(d[9]), "+f"(d[10]), "+f"(d[11]), "+f"(d[12]), "+f"(d[13]), "+f"(d[14]), "+f"(d[15]),
          "+f"(d[16]), "+f"(d[17]), "+f"(d[18]), "+f"(d[19]), "+f"(d[20]), "+f"(d[21]), "+f"(d[22]), "+f"(d[23]),
          "+f"(d[24]), "+f"(d[25]), "+f"(d[26]), "+f"(d[27]), "+f"(d[28]), "+f"(d[29]), "+f"(d[30]), "+f"(d[31]),
          "+f"(d[32]), "+f"(d[33]), "+f"(d[34]), "+f"(d[35]), "+f"(d[36]), "+f"(d[37]), "+f"(d[38]), "+f"(d[39]),
          "+f"(d[40]), "+f"(d[41]), "+f"(d[42]), "+f"(d[43]), "+f"(d[44]), "+f"(d[45]), "+f"(d[46]), "+f"(d[47]),
          "+f"(d[48]), "+f"(d[49]), "+f"(d[50]), "+f"(d[51]), "+f"(d[52]), "+f"(d[53]), "+f"(d[54]), "+f"(d[55]),
          "+f"(d[56]), "+f"(d[57]), "+f"(d[58]), "+f"(d[59]), "+f"(d[60]), "+f"(d[61]), "+f"(d[62]), "+f"(d[63])
        : "l"(da), "l"(db), "r"(scale_d));
}

__device__ __forceinline__ void wgmma_m64n128k16_rs(float* d, const uint32_t* a, uint64_t db, int scale_d) {
    asm volatile(
        "{\n.reg .pred p;\nsetp.ne.b32 p, %69, 0;\n"
        "wgmma.mma_async.sync.aligned.m64n128k16.f32.bf16.bf16 "
        "{%0,%1,%2,%3,%4,%5,%6,%7,%8,%9,%10,%11,%12,%13,%14,%15,"
        "%16,%17,%18,%19,%20,%21,%22,%23,%24,%25,%26,%27,%28,%29,%30,%31,"
        "%32,%33,%34,%35,%36,%37,%38,%39,%40,%41,%42,%43,%44,%45,%46,%47,"
        "%48,%49,%50,%51,%52,%53,%54,%55,%56,%57,%58,%59,%60,%61,%62,%63},"
        " {%64,%65,%66,%67}, %68, p, 1, 1, 0;\n}\n"
        : "+f"(d[0]), "+f"(d[1]), "+f"(d[2]), "+f"(d[3]), "+f"(d[4]), "+f"(d[5]), "+f"(d[6]), "+f"(d[7]),
          "+f"(d[8]), "+f"(d[9]), "+f"(d[10]), "+f"(d[11]), "+f"(d[12]), "+f"(d[13]), "+f"(d[14]), "+f"(d[15]),
          "+f"(d[16]), "+f"(d[17]), "+f"(d[18]), "+f"(d[19]), "+f"(d[20]), "+f"(d[21]), "+f"(d[22]), "+f"(d[23]),
          "+f"(d[24]), "+f"(d[25]), "+f"(d[26]), "+f"(d[27]), "+f"(d[28]), "+f"(d[29]), "+f"(d[30]), "+f"(d[31]),
          "+f"(d[32]), "+f"(d[33]), "+f"(d[34]), "+f"(d[35]), "+f"(d[36]), "+f"(d[37]), "+f"(d[38]), "+f"(d[39]),
          "+f"(d[40]), "+f"(d[41]), "+f"(d[42]), "+f"(d[43]), "+f"(d[44]), "+f"(d[45]), "+f"(d[46]), "+f"(d[47]),
          "+f"(d[48]), "+f"(d[49]), "+f"(d[50]), "+f"(d[51]), "+f"(d[52]), "+f"(d[53]), "+f"(d[54]), "+f"(d[55]),
          "+f"(d[56]), "+f"(d[57]), "+f"(d[58]), "+f"(d[59]), "+f"(d[60]), "+f"(d[61]), "+f"(d[62]), "+f"(d[63])
        : "r"(a[0]), "r"(a[1]), "r"(a[2]), "r"(a[3]), "l"(db), "r"(scale_d));
}
__device__ __forceinline__ void stmatrix_x4_t(uint32_t addr, uint32_t r0, uint32_t r1, uint32_t r2, uint32_t r3) {
    asm volatile("stmatrix.sync.aligned.m8n8.x4.trans.shared.b16 [%0], {%1,%2,%3,%4};" :: "r"(addr), "r"(r0), "r"(r1), "r"(r2), "r"(r3) : "memory");
}
template <int R> __device__ __forceinline__ void reg_alloc() { asm volatile("setmaxnreg.inc.sync.aligned.u32 %0;" :: "n"(R)); }
template <int R> __device__ __forceinline__ void reg_dealloc() { asm volatile("setmaxnreg.dec.sync.aligned.u32 %0;" :: "n"(R)); }

struct GemmWParams {
    CUtensorMap tmA;
    CUtensorMap tmB[3];
    CUtensorMap tmC;
    int ntiles_per_mat;
    int c_col64[3];
    int m_splits;
    int mtiles_per_cta;
    int flag_mats;
    unsigned int* flags;
};

constexpr int GW_NST = 11;
constexpr int GW_SMEM = GW_NST * 16384 + 32768 + 256;

__global__ void __launch_bounds__(384, 1) gemm_w_kernel(const __grid_constant__ GemmWParams p) {
    extern __shared__ __align__(1024) unsigned char smem[];
    const uint32_t sA = smem_u32(smem);
    const uint32_t sOut = sA + GW_NST * 16384;
    const uint32_t bars = sOut + 32768;
    const uint32_t barFull = bars, barEmpty = bars + 8 * GW_NST;
    const int warp = __shfl_sync(0xffffffff, threadIdx.x >> 5, 0), lane = threadIdx.x & 31;

    const int gnt = blockIdx.x / p.m_splits;
    const int ms = blockIdx.x % p.m_splits;
    const int mat = gnt / p.ntiles_per_mat;
    const int nt = gnt % p.ntiles_per_mat;
    const int tile0 = ms * p.mtiles_per_cta;
    const int ntl = p.mtiles_per_cta;

    if (threadIdx.x == 0) {
        for (int i = 0; i < GW_NST; i++) { mbar_init(barFull + 8 * i, 1); mbar_init(barEmpty + 8 * i, 8); }
        fence_mbar_init();
    }
    __syncthreads();

    const int wgi = __shfl_sync(0xffffffff, threadIdx.x >> 7, 0);
    if (wgi == 0) {
        reg_dealloc<40>();
        if (warp == 0 && lane == 0) {
            const CUtensorMap* tmB = &p.tmB[mat];
            const int total = 8 + ntl * 8;
            for (int idx = 0; idx < total; idx++) {
                int slot = idx % GW_NST;
                if (idx >= GW_NST) mbar_wait(barEmpty + 8 * slot, ((idx / GW_NST) - 1) & 1);
                mbar_expect_tx(barFull + 8 * slot, 16384);
                if (idx < 8) tma_load_3d(sA + slot * 16384, tmB, 0, idx * 64, nt * 2, barFull + 8 * slot);
                else {
                    int t = (idx - 8) >> 3, j = (idx - 8) & 7;
                    tma_load_3d(sA + slot * 16384, &p.tmA, 0, (tile0 + t) * 128, j, barFull + 8 * slot);
                }
            }
        }
    } else {
        reg_alloc<232>();
        const int wg = (warp >> 2) - 1, wq = warp & 3;
        uint32_t w[32][4];
        float acc[64];
        {
            const int krow = (lane & 7) + ((lane >> 4) & 1) * 8;
            const int chunk = wq * 2 + ((lane >> 3) & 1);
#pragma unroll
            for (int kb = 0; kb < 8; kb++) {
                mbar_wait(barFull + 8 * kb, 0);
#pragma unroll
                for (int kk = 0; kk < 4; kk++) {
                    int r = kk * 16 + krow;
                    uint32_t addr = sA + kb * 16384 + wg * 8192 + r * 128 + ((chunk ^ (r & 7)) << 4);
                    ldmatrix_x4_t(w[kb * 4 + kk][0], w[kb * 4 + kk][1], w[kb * 4 + kk][2], w[kb * 4 + kk][3], addr);
                }
                __syncwarp();
                if (lane == 0) mbar_arrive(barEmpty + 8 * kb);
            }
        }
        const bool do_flag = (p.flags != nullptr) && (mat < p.flag_mats);
        const int tid_wg = threadIdx.x & 127;
        int pend_tile = -1;
        int idx = 8;
        for (int t = 0; t < ntl; t++) {
            int prev_slot = 0;
            if (wg == 0) { if (t > 0) named_bar_sync(3, 256); }
            else named_bar_sync(4, 256);
#pragma unroll
            for (int j = 0; j < 8; j++, idx++) {
                int slot = idx % GW_NST;
                mbar_wait(barFull + 8 * slot, (idx / GW_NST) & 1);
                wg_fence();
                uint64_t db = make_desc(sA + slot * 16384, 16, 1024);
#pragma unroll
                for (int kk = 0; kk < 4; kk++)
                    wgmma_m64n128k16_rs(acc, w[j * 4 + kk], db + (uint64_t)(kk * 2), (j | kk) != 0);
                wg_commit();
                if (j == 7) {
                    if (wg == 0) named_bar_arrive(4, 256);
                    else if (t + 1 < ntl) named_bar_arrive(3, 256);
                }
                if (j > 0) {
                    wg_wait<1>();
                    if (lane == 0) mbar_arrive(barEmpty + 8 * prev_slot);
                }
                prev_slot = slot;
            }
            wg_wait<0>();
            if (lane == 0) mbar_arrive(barEmpty + 8 * prev_slot);
            if (tid_wg == 0 && pend_tile >= 0) {
                if (do_flag) {
                    bulk_wait_all0();
                    fence_proxy_async_all();
                    __threadfence();
                    atomicAdd(p.flags + pend_tile, 1u);
                } else bulk_wait_read0();
            }
            named_bar_sync(1 + wg, 128);
            const uint32_t sbase = sOut + wg * 16384;
            const int mid = lane >> 3;
            const int chunk = wq * 2 + (mid & 1);
#pragma unroll
            for (int nb = 0; nb < 8; nb++) {
                const int a0 = nb * 8;
                uint32_t r0 = pack_bf16(acc[a0 + 0], acc[a0 + 1]);
                uint32_t r1 = pack_bf16(acc[a0 + 2], acc[a0 + 3]);
                uint32_t r2 = pack_bf16(acc[a0 + 4], acc[a0 + 5]);
                uint32_t r3 = pack_bf16(acc[a0 + 6], acc[a0 + 7]);
                int tok = nb * 16 + (mid >> 1) * 8 + (lane & 7);
                stmatrix_x4_t(sbase + tok * 128 + ((chunk ^ (tok & 7)) << 4), r0, r1, r2, r3);
            }
            fence_proxy_async_smem();
            named_bar_sync(1 + wg, 128);
            if (tid_wg == 0) {
                tma_store_3d(&p.tmC, sbase, 0, (tile0 + t) * 128, p.c_col64[mat] + nt * 2 + wg);
                bulk_commit();
            }
            pend_tile = tile0 + t;
        }
        if (pend_tile >= 0 && tid_wg == 0) {
            bulk_wait_all0();
            if (do_flag) {
                fence_proxy_async_all();
                __threadfence();
                atomicAdd(p.flags + pend_tile, 1u);
            }
        }
    }
}

#define PACE 0
#define NSTEPS 64
#define POLL_B 1
#define POLL_R 1
struct ChainParams {
    CUtensorMap tmW[3];
    CUtensorMap tmWo;
    CUtensorMap tmKV;
    const bf16* mem0;
    bf16* kvmem;
    float* part;
    uint4* membuf;
    const unsigned int* flags;
    unsigned int flag_target;
    unsigned int* seg_flags;
    long long* dbg;
};

constexpr int CH_MEM_STRIDE = 1040;
constexpr int CH_Q_STRIDE = 144;
constexpr int CH_O_STRIDE = 272;
constexpr int CH_NKV = 4;
constexpr int CH_KV_BYTES = 15360;
constexpr int CH_OFF_WO = 0;
constexpr int CH_OFF_WV = 65536;
constexpr int CH_OFF_KV = 131072;
constexpr int CH_OFF_MEM = CH_OFF_KV + CH_NKV * CH_KV_BYTES;
constexpr int CH_OFF_RS = CH_OFF_MEM + 8192;
constexpr int CH_OFF_STG = CH_OFF_RS + 8192;
constexpr int CH_OFF_Q = CH_OFF_STG + 512;
constexpr int CH_OFF_O = CH_OFF_Q + 1152;
constexpr int CH_OFF_RED1 = CH_OFF_O + 2176;
constexpr int CH_OFF_SC = CH_OFF_RED1 + 6144;
constexpr int CH_OFF_RED2 = CH_OFF_SC + 1280;
constexpr int CH_OFF_ZERO = CH_OFF_RED2 + 2048;
constexpr int CH_OFF_BAR = CH_OFF_ZERO + 128;
constexpr int CH_OFF_TS = CH_OFF_BAR + 256;
constexpr int CH_SMEM = CH_OFF_TS + 1024;

__device__ __forceinline__ uint32_t mapa_u32(uint32_t addr, uint32_t rank) {
    uint32_t r; asm volatile("mapa.shared::cluster.u32 %0, %1, %2;" : "=r"(r) : "r"(addr), "r"(rank)); return r;
}
__device__ __forceinline__ void st_async_v4(uint32_t addr, uint32_t a, uint32_t b, uint32_t c, uint32_t d, uint32_t mbar) {
    asm volatile("st.async.shared::cluster.mbarrier::complete_tx::bytes.v4.b32 [%0], {%1,%2,%3,%4}, [%5];"
                 :: "r"(addr), "r"(a), "r"(b), "r"(c), "r"(d), "r"(mbar) : "memory");
}
__device__ __forceinline__ void st_async_v2(uint32_t addr, uint32_t a, uint32_t b, uint32_t mbar) {
    asm volatile("st.async.shared::cluster.mbarrier::complete_tx::bytes.v2.b32 [%0], {%1,%2}, [%3];"
                 :: "r"(addr), "r"(a), "r"(b), "r"(mbar) : "memory");
}
__device__ __forceinline__ bool mbar_try_wait_cl(uint32_t bar, uint32_t parity) {
    uint32_t ok;
    asm volatile("{\n.reg .pred p;\nmbarrier.try_wait.parity.acquire.cluster.shared::cta.b64 p, [%1], %2;\nselp.u32 %0, 1, 0, p;\n}"
                 : "=r"(ok) : "r"(bar), "r"(parity) : "memory");
    return ok != 0;
}
__device__ __forceinline__ void mbar_wait_cl(uint32_t bar, uint32_t parity) {
    uint32_t n = 0;
    while (!mbar_try_wait_cl(bar, parity)) { if (++n > (1u << 20)) break; }
}
__device__ __forceinline__ void cluster_sync_all() {
    asm volatile("barrier.cluster.arrive.aligned;\nbarrier.cluster.wait.aligned;" ::: "memory");
}
__device__ __forceinline__ uint4 ld_relaxed_v4(const void* p) {
    uint4 v;
    asm volatile("ld.relaxed.gpu.global.v4.u32 {%0,%1,%2,%3}, [%4];" : "=r"(v.x), "=r"(v.y), "=r"(v.z), "=r"(v.w) : "l"(p) : "memory");
    return v;
}
__device__ __forceinline__ void st_relaxed_v4(void* p, uint32_t a, uint32_t b, uint32_t c, uint32_t d) {
    asm volatile("st.relaxed.gpu.global.v4.u32 [%0], {%1,%2,%3,%4};" :: "l"(p), "r"(a), "r"(b), "r"(c), "r"(d) : "memory");
}
__device__ __forceinline__ unsigned int ld_acquire_u32(const unsigned int* p) {
    unsigned int v;
    asm volatile("ld.acquire.gpu.global.u32 %0, [%1];" : "=r"(v) : "l"(p) : "memory");
    return v;
}
__device__ __forceinline__ void lds128(uint32_t* r, uint32_t addr) {
    asm volatile("ld.shared.v4.u32 {%0,%1,%2,%3}, [%4];" : "=r"(r[0]), "=r"(r[1]), "=r"(r[2]), "=r"(r[3]) : "r"(addr) : "memory");
}
__device__ __forceinline__ float ex2_approx(float x) { float y; asm("ex2.approx.ftz.f32 %0, %1;" : "=f"(y) : "f"(x)); return y; }
__device__ __forceinline__ void mma_nv(float* c, const uint32_t* a, uint32_t b0, uint32_t b1) {
    asm("mma.sync.aligned.m16n8k16.row.col.f32.bf16.bf16.f32 {%0,%1,%2,%3}, {%4,%5,%6,%7}, {%8,%9}, {%0,%1,%2,%3};"
        : "+f"(c[0]), "+f"(c[1]), "+f"(c[2]), "+f"(c[3]) : "r"(a[0]), "r"(a[1]), "r"(a[2]), "r"(a[3]), "r"(b0), "r"(b1));
}

__device__ __forceinline__ void st_relaxed_v2(void* p, uint32_t a, uint32_t b) {
    asm volatile("st.relaxed.gpu.global.v2.u32 [%0], {%1,%2};" :: "l"(p), "r"(a), "r"(b) : "memory");
}

#define TSX(i)
__global__ void __launch_bounds__(384, 1) chain_kernel(const __grid_constant__ ChainParams p) {
    extern __shared__ __align__(1024) unsigned char smem[];
    const uint32_t sb = smem_u32(smem);
    int tid; asm volatile("mov.u32 %0, %%tid.x;" : "=r"(tid));
    int bid; asm volatile("mov.u32 %0, %%ctaid.x;" : "=r"(bid));
    const int lane = tid & 31;
    const int warp = __shfl_sync(0xffffffff, tid >> 5, 0);
    const int wgi = __shfl_sync(0xffffffff, tid >> 7, 0);
    const int rank = bid & 15, cl = bid >> 4;
    const int head = bid >> 1, half = bid & 1;
    const uint32_t barSc = sb + CH_OFF_BAR, barV = barSc + 8, barLd = barSc + 16, barKV = barSc + 24, barMem = barKV + 8 * CH_NKV, barRS = barMem + 8;

    if (tid == 0) {
        mbar_init(barSc, 1); mbar_init(barV, 1); mbar_init(barLd, 1); mbar_init(barMem, 1); mbar_init(barRS, 1);
        for (int i = 0; i < CH_NKV; i++) mbar_init(barKV + 8 * i, 1);
        fence_mbar_init();
        mbar_expect_tx(barSc, 1280);
        mbar_expect_tx(barV, 1024);
        mbar_expect_tx(barMem, 8192);
        mbar_expect_tx(barRS, 8192);
    }
    if (tid < 32) *reinterpret_cast<uint32_t*>(smem + CH_OFF_ZERO + tid * 4) = 0u;
    __syncthreads();
    cluster_sync_all();
    asm volatile("griddepcontrol.launch_dependents;" ::: "memory");
    const uint32_t peer = rank ^ 1;
    const int t4 = lane & 3, g8 = lane >> 2;
    const int lr = lane & 7, lm = lane >> 3;

    if (wgi < 2) {
        reg_alloc<208>();
        const int g = warp >> 1, kh = warp & 1;
        uint32_t wqk[2][16][4];
        {
            const int c64 = head * 2 + half;
            const int krow = lr + ((lane >> 4) & 1) * 8;
            const int chunk = g * 2 + (lm & 1);
            if (tid == 0) {
                mbar_expect_tx(barLd, 131072);
                tma_load_3d(sb + CH_OFF_WO, &p.tmW[0], 0, 0, c64, barLd);
                tma_load_3d(sb + CH_OFF_WO + 32768, &p.tmW[0], 0, 256, c64, barLd);
                tma_load_3d(sb + CH_OFF_WV, &p.tmW[1], 0, 0, c64, barLd);
                tma_load_3d(sb + CH_OFF_WV + 32768, &p.tmW[1], 0, 256, c64, barLd);
            }
            mbar_wait(barLd, 0);
#pragma unroll
            for (int m = 0; m < 2; m++)
#pragma unroll
                for (int ks = 0; ks < 16; ks++) {
                    int r = kh * 256 + ks * 16 + krow;
                    uint32_t addr = sb + (m == 0 ? CH_OFF_WO : CH_OFF_WV) + r * 128 + ((chunk ^ (r & 7)) << 4);
                    ldmatrix_x4_t(wqk[m][ks][0], wqk[m][ks][1], wqk[m][ks][2], wqk[m][ks][3], addr);
                }
            named_bar_sync(7, 256);
            if (tid == 0) {
                mbar_expect_tx(barLd, 131072);
                tma_load_3d(sb + CH_OFF_WV, &p.tmW[2], 0, 0, c64, barLd);
                tma_load_3d(sb + CH_OFF_WV + 32768, &p.tmW[2], 0, 256, c64, barLd);
                for (int i = 0; i < 4; i++) tma_load_3d(sb + CH_OFF_WO + i * 16384, &p.tmWo, 0, head * 128, half * 4 + i, barLd);
            }
            mbar_wait(barLd, 1);
            uint32_t f[16][4];
#pragma unroll
            for (int ks = 0; ks < 16; ks++) {
                int r = kh * 256 + ks * 16 + krow;
                ldmatrix_x4_t(f[ks][0], f[ks][1], f[ks][2], f[ks][3], sb + CH_OFF_WV + r * 128 + ((chunk ^ (r & 7)) << 4));
            }
            named_bar_sync(7, 256);
#pragma unroll
            for (int ks = 0; ks < 16; ks++)
                asm volatile("st.shared.v4.u32 [%0], {%1,%2,%3,%4};" :: "r"(sb + CH_OFF_WV + ((warp * 16 + ks) * 32 + lane) * 16), "r"(f[ks][0]), "r"(f[ks][1]), "r"(f[ks][2]), "r"(f[ks][3]) : "memory");
#pragma unroll
            for (int ks = 0; ks < 8; ks++)
#pragma unroll
                for (int mt = 0; mt < 2; mt++) {
                    int r = ks * 16 + krow;
                    int colchunk = warp * 4 + mt * 2 + (lm & 1);
                    ldmatrix_x4_t(f[ks * 2 + mt][0], f[ks * 2 + mt][1], f[ks * 2 + mt][2], f[ks * 2 + mt][3],
                                  sb + CH_OFF_WO + (colchunk >> 3) * 16384 + r * 128 + (((colchunk & 7) ^ (r & 7)) << 4));
                }
            named_bar_sync(7, 256);
#pragma unroll
            for (int i = 0; i < 16; i++)
                asm volatile("st.shared.v4.u32 [%0], {%1,%2,%3,%4};" :: "r"(sb + CH_OFF_WO + ((warp * 16 + i) * 32 + lane) * 16), "r"(f[i][0]), "r"(f[i][1]), "r"(f[i][2]), "r"(f[i][3]) : "memory");
            named_bar_sync(7, 256);
        }
        const uint32_t wvbase = sb + CH_OFF_WV + (warp * 16 * 32 + lane) * 16;
        const uint32_t wobase = sb + CH_OFF_WO + (warp * 16 * 32 + lane) * 16;
        const uint32_t bAddr = sb + CH_OFF_MEM + kh * 4096 + lr * 64 + ((lm ^ ((lr >> 1) & 3)) << 4);
        const uint32_t redMine = sb + CH_OFF_RED1 + warp * 512 + lane * 16, redOther = sb + CH_OFF_RED1 + (warp ^ 1) * 512 + lane * 16;
        const uint32_t redMineV = sb + CH_OFF_RED1 + 4096 + warp * 256 + lane * 8, redOtherV = sb + CH_OFF_RED1 + 4096 + (warp ^ 1) * 256 + lane * 8;
        const uint32_t qDst = sb + CH_OFF_Q + lr * CH_Q_STRIDE + (g * 16 + (lm & 1) * 8) * 2;
        const uint32_t kvOff = lr * 128 + (((g * 2 + (lm & 1)) ^ lr) << 4);
        const uint32_t peerBase = mapa_u32(sb, peer) - sb;
        const uint32_t oAddr = sb + CH_OFF_O + lr * CH_O_STRIDE + lm * 16;
        const uint32_t rsDst = mapa_u32(sb + CH_OFF_RS + (rank >> 1) * 1024 + lane * 16, warp * 2 + half);
        const uint32_t rsBar = mapa_u32(barRS, warp * 2 + half);
        float* llW = p.part + ((size_t)(cl * 16 + rank) * 64 + tid) * 4;
        for (int s = 0; s < NSTEPS; s++) {
            const uint32_t sKV = sb + CH_OFF_KV + (s & (CH_NKV - 1)) * CH_KV_BYTES;
            uint32_t wo[16][4], wv[2][2][4];
#pragma unroll
            for (int i = 0; i < 8; i++) lds128(wo[i], wobase + i * 512);
            lds128(wv[0][0], wvbase); lds128(wv[0][1], wvbase + 512);
            TSX(0);
            if (s == 0) {
                for (int i = tid; i < 512; i += 256) {
                    int tok = i & 7, c = i >> 3;
                    uint4 v = *reinterpret_cast<const uint4*>(p.mem0 + tok * 512 + c * 8);
                    *reinterpret_cast<uint4*>(smem + CH_OFF_MEM + (c >> 2) * 512 + tok * 64 + (((c & 3) ^ ((tok >> 1) & 3)) << 4)) = v;
                }
                named_bar_sync(7, 256);
            } else {
                mbar_wait(barMem, (s - 1) & 1);
                if (tid == 0) mbar_expect_tx(barMem, 8192);
            }
            TSX(1);
            {
                float aq[4], ak[4], av[4];
#pragma unroll
                for (int i = 0; i < 4; i++) { aq[i] = ak[i] = av[i] = 0.f; }
                uint32_t b[2][4];
                ldmatrix_x4(b[0][0], b[0][1], b[0][2], b[0][3], bAddr);
#pragma unroll
                for (int kk = 0; kk < 8; kk++) {
                    if (kk + 1 < 8) {
                        ldmatrix_x4(b[(kk + 1) & 1][0], b[(kk + 1) & 1][1], b[(kk + 1) & 1][2], b[(kk + 1) & 1][3], bAddr + (kk + 1) * 512);
                        lds128(wv[(kk + 1) & 1][0], wvbase + (2 * kk + 2) * 512);
                        lds128(wv[(kk + 1) & 1][1], wvbase + (2 * kk + 3) * 512);
                    }
                    mma_nv(aq, wqk[0][2 * kk], b[kk & 1][0], b[kk & 1][1]);
                    mma_nv(ak, wqk[1][2 * kk], b[kk & 1][0], b[kk & 1][1]);
                    mma_nv(av, wv[kk & 1][0], b[kk & 1][0], b[kk & 1][1]);
                    mma_nv(aq, wqk[0][2 * kk + 1], b[kk & 1][2], b[kk & 1][3]);
                    mma_nv(ak, wqk[1][2 * kk + 1], b[kk & 1][2], b[kk & 1][3]);
                    mma_nv(av, wv[kk & 1][1], b[kk & 1][2], b[kk & 1][3]);
                }
                TSX(2);
                float gv[6], kp[6];
#pragma unroll
                for (int i = 0; i < 4; i++) {
                    gv[i] = kh == 0 ? ak[i] : aq[i];
                    kp[i] = kh == 0 ? aq[i] : ak[i];
                }
                gv[4] = kh == 0 ? av[2] : av[0]; gv[5] = kh == 0 ? av[3] : av[1];
                kp[4] = kh == 0 ? av[0] : av[2]; kp[5] = kh == 0 ? av[1] : av[3];
                asm volatile("st.shared.v4.f32 [%0], {%1,%2,%3,%4};" :: "r"(redMine), "f"(gv[0]), "f"(gv[1]), "f"(gv[2]), "f"(gv[3]) : "memory");
                asm volatile("st.shared.v2.f32 [%0], {%1,%2};" :: "r"(redMineV), "f"(gv[4]), "f"(gv[5]) : "memory");
                named_bar_sync(1 + g, 64);
                float o0, o1, o2, o3, o4, o5;
                asm volatile("ld.shared.v4.f32 {%0,%1,%2,%3}, [%4];" : "=f"(o0), "=f"(o1), "=f"(o2), "=f"(o3) : "r"(redOther) : "memory");
                asm volatile("ld.shared.v2.f32 {%0,%1}, [%2];" : "=f"(o4), "=f"(o5) : "r"(redOtherV) : "memory");
                uint32_t r0 = pack_bf16(kp[0] + o0, kp[1] + o1);
                uint32_t r1 = pack_bf16(kp[2] + o2, kp[3] + o3);
                uint32_t r2 = pack_bf16(kp[4] + o4, kp[5] + o5);
                asm volatile("stmatrix.sync.aligned.m8n8.x2.trans.shared.b16 [%0], {%1,%2};" :: "r"(kh == 0 ? qDst : sKV + kvOff), "r"(r0), "r"(r1) : "memory");
                const uint32_t vAddr = sKV + 5120 + half * 5120 + lr * 128 + (((g * 2 + kh) ^ lr) << 4);
                asm volatile("stmatrix.sync.aligned.m8n8.x1.trans.shared.b16 [%0], {%1};" :: "r"(vAddr), "r"(r2) : "memory");
                named_bar_arrive(5, 384);
                TSX(3);
                __syncwarp();
                if (lane < 8) {
                    uint32_t f[4];
                    lds128(f, vAddr);
                    st_async_v4(vAddr + peerBase, f[0], f[1], f[2], f[3], barV + peerBase);
                }
            }
            if (s == NSTEPS - 1) break;
            named_bar_sync(10, 384);
#pragma unroll
            for (int i = 8; i < 16; i++) {
                lds128(wo[i], wobase + i * 512);
            }
            TSX(4);
            named_bar_sync(8, 384);
            TSX(5);
            const uint32_t tag = ((s >> 1) + 1) & 1;
            const uint32_t slotOff = (s & 1) * (64 * 256);
            {
                float a2[2][2][4];
#pragma unroll
                for (int i = 0; i < 4; i++) { a2[0][0][i] = a2[0][1][i] = a2[1][0][i] = a2[1][1][i] = 0.f; }
                uint32_t b[4][4];
#pragma unroll
                for (int kk = 0; kk < 4; kk++) ldmatrix_x4(b[kk][0], b[kk][1], b[kk][2], b[kk][3], oAddr + kk * 64);
#pragma unroll
                for (int kk = 0; kk < 4; kk++) {
                    mma_nv(a2[0][0], wo[kk * 4 + 0], b[kk][0], b[kk][1]);
                    mma_nv(a2[1][0], wo[kk * 4 + 1], b[kk][0], b[kk][1]);
                    mma_nv(a2[0][1], wo[kk * 4 + 2], b[kk][2], b[kk][3]);
                    mma_nv(a2[1][1], wo[kk * 4 + 3], b[kk][2], b[kk][3]);
                }
#pragma unroll
                for (int mt = 0; mt < 2; mt++) {
                    float c0 = a2[mt][0][0] + a2[mt][1][0], c1 = a2[mt][0][1] + a2[mt][1][1];
                    float c2 = a2[mt][0][2] + a2[mt][1][2], c3 = a2[mt][0][3] + a2[mt][1][3];
                    st_async_v4(rsDst + mt * 512, __float_as_uint(c0), __float_as_uint(c1), __float_as_uint(c2), __float_as_uint(c3), rsBar);
                }
            }
            TSX(6);
            if (warp < 2) {
                mbar_wait(barRS, s & 1);
                TSX(7);
                float4 u[8];
#pragma unroll
                for (int h = 0; h < 8; h++)
                    asm volatile("ld.shared.v4.f32 {%0,%1,%2,%3}, [%4];" : "=f"(u[h].x), "=f"(u[h].y), "=f"(u[h].z), "=f"(u[h].w) : "r"(sb + CH_OFF_RS + h * 1024 + tid * 16) : "memory");
                if (tid == 0) mbar_expect_tx(barRS, 8192);
                float f0 = ((u[0].x + u[1].x) + (u[2].x + u[3].x)) + ((u[4].x + u[5].x) + (u[6].x + u[7].x));
                float f1 = ((u[0].y + u[1].y) + (u[2].y + u[3].y)) + ((u[4].y + u[5].y) + (u[6].y + u[7].y));
                float f2 = ((u[0].z + u[1].z) + (u[2].z + u[3].z)) + ((u[4].z + u[5].z) + (u[6].z + u[7].z));
                float f3 = ((u[0].w + u[1].w) + (u[2].w + u[3].w)) + ((u[4].w + u[5].w) + (u[6].w + u[7].w));
                const uint32_t x0 = (__float_as_uint(f0) & ~1u) | tag;
                st_relaxed_v4(llW + slotOff, x0, __float_as_uint(f1), __float_as_uint(f2), __float_as_uint(f3));
                const float* r1 = p.part + slotOff + ((size_t)((cl ^ 1) * 16 + rank) * 64 + tid) * 4;
                const float* r2 = p.part + slotOff + ((size_t)((cl ^ 2) * 16 + rank) * 64 + tid) * 4;
                const float* r3 = p.part + slotOff + ((size_t)((cl ^ 3) * 16 + rank) * 64 + tid) * 4;
                uint4 v1, v2, v3;
                uint32_t n = 0;
                do { v1 = ld_relaxed_v4(r1); v2 = ld_relaxed_v4(r2); v3 = ld_relaxed_v4(r3); }
                while (POLL_R && (((v1.x ^ tag) | (v2.x ^ tag) | (v3.x ^ tag)) & 1u) && ++n < (1u << 22));
                TSX(8);
                f0 = (__uint_as_float(x0) + __uint_as_float(v1.x)) + (__uint_as_float(v2.x) + __uint_as_float(v3.x));
                f1 = (f1 + __uint_as_float(v1.y)) + (__uint_as_float(v2.y) + __uint_as_float(v3.y));
                f2 = (f2 + __uint_as_float(v1.z)) + (__uint_as_float(v2.z) + __uint_as_float(v3.z));
                f3 = (f3 + __uint_as_float(v1.w)) + (__uint_as_float(v2.w) + __uint_as_float(v3.w));
                const int ch = warp * 2 + (lm & 1);
                asm volatile("stmatrix.sync.aligned.m8n8.x2.trans.shared.b16 [%0], {%1,%2};"
                             :: "r"(sb + CH_OFF_STG + lr * 64 + ((ch ^ ((lr >> 1) & 3)) << 4)), "r"(pack_bf16(f0, f1)), "r"(pack_bf16(f2, f3)) : "memory");
                named_bar_sync(9, 64);
                uint32_t f[4];
                lds128(f, sb + CH_OFF_STG + lane * 16);
                const uint32_t dst0 = sb + CH_OFF_MEM + (half * 8 + (rank >> 1)) * 512 + lane * 16;
#pragma unroll
                for (int d = 0; d < 8; d++) {
                    const uint32_t dr = warp * 8 + d;
                    st_async_v4(mapa_u32(dst0, dr), f[0], f[1], f[2], f[3], mapa_u32(barMem, dr));
                }
                TSX(9);
            }
        }
    } else {
        reg_dealloc<88>();
        const int aw = warp - 8;
        const uint32_t peerBase = mapa_u32(sb, peer) - sb;
        const float sm_scale = 0.08838834764831845f * 1.4426950408889634f;
        const int kc64 = 64 + head * 2 + half, vc64 = 128 + head * 2;
        auto issue_kv = [&](int s) {
            if ((s & 3) == 0) {
                uint32_t n = 0;
                while (ld_acquire_u32(p.flags + (s >> 2)) < p.flag_target) { if (++n > (1u << 22)) break; }
                fence_proxy_async_all();
            }
            int st = s & (CH_NKV - 1);
            uint32_t base = sb + CH_OFF_KV + st * CH_KV_BYTES;
            mbar_expect_tx(barKV + 8 * st, 12288);
            tma_load_3d(base + 1024, &p.tmKV, 0, s * 32, kc64, barKV + 8 * st);
            tma_load_3d(base + 5120 + 1024, &p.tmKV, 0, s * 32, vc64, barKV + 8 * st);
            tma_load_3d(base + 10240 + 1024, &p.tmKV, 0, s * 32, vc64 + 1, barKV + 8 * st);
        };
        if (aw == 3 && lane == 0) { for (int s = 0; s < CH_NKV - 1; s++) issue_kv(s); }
        const uint32_t kOff0 = lr * 128 + ((lm ^ lr) << 4), kOff1 = lr * 128 + (((4 + lm) ^ lr) << 4);
        const uint32_t qAddr = (lm & 1) ? (sb + CH_OFF_ZERO) : (sb + CH_OFF_Q + lr * CH_Q_STRIDE + (lm >> 1) * 16);
        const uint32_t qStep = (lm & 1) ? 0u : 32u;
        const uint32_t vRow = ((lm >> 1) * 8 + lr) * 128;
        const uint32_t vOff0 = 5120 + (aw >> 1) * 5120 + vRow + ((((aw & 1) * 4 + (lm & 1)) ^ lr) << 4);
        const uint32_t vOff1 = 5120 + (aw >> 1) * 5120 + vRow + ((((aw & 1) * 4 + 2 + (lm & 1)) ^ lr) << 4);
        const uint32_t padAdj = (lm >> 1) ? 2048u : 0u;
        const uint32_t scAddr = sb + CH_OFF_SC + lane * 8;
        const uint32_t oDst = sb + CH_OFF_O + lr * CH_O_STRIDE + (aw * 32 + lm * 8) * 2;
        const int si = tid - 256, sw = si >> 6, stok = (si >> 3) & 7, scn = si & 7;
        const uint32_t kvmOff = (sw == 0 ? 0u : 5120u + half * 5120u) + stok * 128 + ((scn ^ stok) << 4);
        bf16* kvmDst = p.kvmem + (size_t)stok * 8192 + sw * 4096 + head * 128 + half * 64 + scn * 8;
        const bool leader = (tid == 256);
        for (int s = 0; s < NSTEPS; s++) {
            const uint32_t par = s & 1;
            const int st = s & (CH_NKV - 1);
            const uint32_t sKV = sb + CH_OFF_KV + st * CH_KV_BYTES;
            mbar_wait(barKV + 8 * st, (s / CH_NKV) & 1);
            uint32_t kb[2][4][4], va[3][2][4];
#pragma unroll
            for (int n = 0; n < 4; n++) {
                ldmatrix_x4(kb[0][n][0], kb[0][n][1], kb[0][n][2], kb[0][n][3], sKV + (n + 1) * 1024 + kOff0);
                ldmatrix_x4(kb[1][n][0], kb[1][n][1], kb[1][n][2], kb[1][n][3], sKV + (n + 1) * 1024 + kOff1);
            }
            TSX(0);
            named_bar_sync(5, 384);
            TSX(1);
            float sc[5][4];
#pragma unroll
            for (int n = 0; n < 5; n++) { sc[n][0] = sc[n][1] = sc[n][2] = sc[n][3] = 0.f; }
            {
                uint32_t a[4][4], km[2][4];
#pragma unroll
                for (int k = 0; k < 4; k++) ldmatrix_x4(a[k][0], a[k][1], a[k][2], a[k][3], qAddr + k * qStep);
                ldmatrix_x4(km[0][0], km[0][1], km[0][2], km[0][3], sKV + kOff0);
                ldmatrix_x4(km[1][0], km[1][1], km[1][2], km[1][3], sKV + kOff1);
#pragma unroll
                for (int kp = 0; kp < 2; kp++) {
#pragma unroll
                    for (int n = 0; n < 4; n++) mma_nv(sc[n + 1], a[kp * 2], kb[kp][n][0], kb[kp][n][1]);
#pragma unroll
                    for (int n = 0; n < 4; n++) mma_nv(sc[n + 1], a[kp * 2 + 1], kb[kp][n][2], kb[kp][n][3]);
                }
                mma_nv(sc[0], a[0], km[0][0], km[0][1]);
                mma_nv(sc[0], a[1], km[0][2], km[0][3]);
                mma_nv(sc[0], a[2], km[1][0], km[1][1]);
                mma_nv(sc[0], a[3], km[1][2], km[1][3]);
            }
            TSX(2);
            if (aw == 0) {
#pragma unroll
                for (int n = 0; n < 5; n++) st_async_v2(scAddr + peerBase + n * 256, __float_as_uint(sc[n][0]), __float_as_uint(sc[n][1]), barSc + peerBase);
            }
#pragma unroll
            for (int ks = 1; ks < 3; ks++) {
                const uint32_t adj = ks == 2 ? padAdj : 0u;
                ldmatrix_x4_t(va[ks][0][0], va[ks][0][1], va[ks][0][2], va[ks][0][3], sKV + ks * 2048 + vOff0 - adj);
                ldmatrix_x4_t(va[ks][1][0], va[ks][1][1], va[ks][1][2], va[ks][1][3], sKV + ks * 2048 + vOff1 - adj);
            }
            uint4 kvm;
            if (s < NSTEPS - 1) named_bar_arrive(10, 384);
            if (sw == 0) asm volatile("ld.shared.v4.u32 {%0,%1,%2,%3}, [%4];" : "=r"(kvm.x), "=r"(kvm.y), "=r"(kvm.z), "=r"(kvm.w) : "r"(sKV + kvmOff) : "memory");
            TSX(3);
            mbar_wait(barSc, par);
            TSX(4);
            float pp[5][2];
#pragma unroll
            for (int n = 0; n < 5; n++)
                asm volatile("ld.shared.v2.f32 {%0,%1}, [%2];" : "=f"(pp[n][0]), "=f"(pp[n][1]) : "r"(scAddr + n * 256) : "memory");
            if (leader) mbar_expect_tx(barSc, 1280);
#pragma unroll
            for (int n = 0; n < 5; n++) { sc[n][0] += pp[n][0]; sc[n][1] += pp[n][1]; }
            float mx = fmaxf(fmaxf(fmaxf(sc[0][0], sc[0][1]), fmaxf(sc[1][0], sc[1][1])), fmaxf(fmaxf(sc[2][0], sc[2][1]), fmaxf(sc[3][0], sc[3][1])));
            mx = fmaxf(mx, fmaxf(sc[4][0], sc[4][1]));
            mx = fmaxf(mx, __shfl_xor_sync(0xffffffff, mx, 1));
            mx = fmaxf(mx, __shfl_xor_sync(0xffffffff, mx, 2));
            const float mb = mx * sm_scale;
            uint32_t pb[5];
            float e[5][2];
#pragma unroll
            for (int n = 0; n < 5; n++) {
                e[n][0] = ex2_approx(fmaf(sc[n][0], sm_scale, -mb));
                e[n][1] = ex2_approx(fmaf(sc[n][1], sm_scale, -mb));
                pb[n] = pack_bf16(e[n][0], e[n][1]);
            }
            TSX(5);
            float oc[2][4];
#pragma unroll
            for (int i = 0; i < 4; i++) { oc[0][i] = oc[1][i] = 0.f; }
            mma_nv(oc[0], va[1][0], pb[2], pb[3]);
            mma_nv(oc[1], va[1][1], pb[2], pb[3]);
            mma_nv(oc[0], va[2][0], pb[4], 0u);
            mma_nv(oc[1], va[2][1], pb[4], 0u);
            float sum = ((e[0][0] + e[0][1]) + (e[1][0] + e[1][1])) + ((e[2][0] + e[2][1]) + (e[3][0] + e[3][1])) + (e[4][0] + e[4][1]);
            sum += __shfl_xor_sync(0xffffffff, sum, 1);
            sum += __shfl_xor_sync(0xffffffff, sum, 2);
            const float inv = __fdividef(1.0f, sum);
            const float i0 = __shfl_sync(0xffffffff, inv, t4 * 8), i1 = __shfl_sync(0xffffffff, inv, t4 * 8 + 4);
            TSX(6);
            mbar_wait(barV, par);
            TSX(7);
            ldmatrix_x4_t(va[0][0][0], va[0][0][1], va[0][0][2], va[0][0][3], sKV + vOff0);
            ldmatrix_x4_t(va[0][1][0], va[0][1][1], va[0][1][2], va[0][1][3], sKV + vOff1);
            if (leader) mbar_expect_tx(barV, 1024);
            if (sw == 1) asm volatile("ld.shared.v4.u32 {%0,%1,%2,%3}, [%4];" : "=r"(kvm.x), "=r"(kvm.y), "=r"(kvm.z), "=r"(kvm.w) : "r"(sKV + kvmOff) : "memory");
            mma_nv(oc[0], va[0][0], pb[0], pb[1]);
            mma_nv(oc[1], va[0][1], pb[0], pb[1]);
            stmatrix_x4_t(oDst, pack_bf16(oc[0][0] * i0, oc[0][1] * i1), pack_bf16(oc[0][2] * i0, oc[0][3] * i1),
                          pack_bf16(oc[1][0] * i0, oc[1][1] * i1), pack_bf16(oc[1][2] * i0, oc[1][3] * i1));
            if (s < NSTEPS - 1) named_bar_arrive(8, 384);
            TSX(8);
            *reinterpret_cast<uint4*>(kvmDst + (size_t)s * 65536) = kvm;
            if (p.seg_flags) { __syncwarp(); if (lane == 0) { __threadfence(); atomicAdd(p.seg_flags + s, 1u); } }
            if (aw == 3 && lane == 0 && s + CH_NKV - 1 < NSTEPS) issue_kv(s + CH_NKV - 1);
        }
    }
    __syncthreads();
    cluster_sync_all();
}

struct AttnAParams {
    CUtensorMap tmKV;
    const bf16* qkv;
    bf16* o;
};
constexpr int AA_KT = 256;
constexpr int AA_NST = 3;
constexpr int AA_SMEM = AA_NST * 2 * AA_KT * 32 + 64;

__device__ __forceinline__ float ex2a(float x) { float y; asm("ex2.approx.ftz.f32 %0, %1;" : "=f"(y) : "f"(x)); return y; }
__device__ __forceinline__ void mma_f(float* c, const uint32_t* a, uint32_t b0, uint32_t b1) {
    asm("mma.sync.aligned.m16n8k16.row.col.f32.bf16.bf16.f32 {%0,%1,%2,%3}, {%4,%5,%6,%7}, {%8,%9}, {%0,%1,%2,%3};"
        : "+f"(c[0]), "+f"(c[1]), "+f"(c[2]), "+f"(c[3]) : "r"(a[0]), "r"(a[1]), "r"(a[2]), "r"(a[3]), "r"(b0), "r"(b1));
}

__global__ void __launch_bounds__(256, 2) attn_a_kernel(const __grid_constant__ AttnAParams p) {
    extern __shared__ __align__(1024) unsigned char smem[];
    const uint32_t sb = smem_u32(smem);
    const uint32_t bars = sb + AA_NST * 2 * AA_KT * 32;
    const int tid = threadIdx.x, lane = tid & 31, warp = tid >> 5;
    const int head = blockIdx.x >> 3, qt = blockIdx.x & 7;
    const int t4 = lane & 3, g8 = lane >> 2;
    constexpr int NT = 2048 / AA_KT;

    if (tid == 0) {
        for (int i = 0; i < AA_NST; i++) { mbar_init(bars + 8 * i, 1); mbar_init(bars + 8 * (AA_NST + i), 8); }
        fence_mbar_init();
    }
    __syncthreads();
    auto issue = [&](int t) {
        int st = t % AA_NST;
        uint32_t dst = sb + st * (2 * AA_KT * 32);
        mbar_expect_tx(bars + 8 * st, 2 * AA_KT * 32);
        tma_load_2d(dst, &p.tmKV, 512 + head * 16, t * AA_KT, bars + 8 * st);
        tma_load_2d(dst + AA_KT * 32, &p.tmKV, 1024 + head * 16, t * AA_KT, bars + 8 * st);
    };
    if (tid == 0) { for (int t = 0; t < AA_NST; t++) issue(t); }

    uint32_t qa[2][4];
    const int row0 = qt * 256 + warp * 32;
#pragma unroll
    for (int m = 0; m < 2; m++) {
        const bf16* q = p.qkv + (size_t)(row0 + m * 16 + g8) * 1536 + head * 16 + t4 * 2;
        qa[m][0] = *reinterpret_cast<const uint32_t*>(q);
        qa[m][1] = *reinterpret_cast<const uint32_t*>(q + 8 * 1536);
        qa[m][2] = *reinterpret_cast<const uint32_t*>(q + 8);
        qa[m][3] = *reinterpret_cast<const uint32_t*>(q + 8 * 1536 + 8);
    }
    const float sc = 0.25f * 1.4426950408889634f;
    float mrow[2][2], oacc[2][2][4], lacc[2][4];
#pragma unroll
    for (int m = 0; m < 2; m++) {
        mrow[m][0] = mrow[m][1] = -3.0e38f;
#pragma unroll
        for (int i = 0; i < 4; i++) { oacc[m][0][i] = oacc[m][1][i] = 0.f; lacc[m][i] = 0.f; }
    }
    const uint32_t ones = 0x3F803F80u;
    const int lr = lane & 7, lm = lane >> 3;
    const int krow = (lm >> 1) * 8 + lr, kch = lm & 1;
    const uint32_t koff = krow * 32 + ((kch ^ ((krow >> 2) & 1)) << 4);
    const int vrow = (lm & 1) * 8 + lr, vch = lm >> 1;
    const uint32_t voff = vrow * 32 + ((vch ^ ((vrow >> 2) & 1)) << 4);

    for (int t = 0; t < NT; t++) {
        const int st = t % AA_NST;
        mbar_wait(bars + 8 * st, (t / AA_NST) & 1);
        const uint32_t sK = sb + st * (2 * AA_KT * 32), sV = sK + AA_KT * 32;
#pragma unroll 1
        for (int kb = 0; kb < AA_KT / 64; kb++) {
            float s[2][8][4];
#pragma unroll
            for (int np = 0; np < 4; np++) {
                uint32_t b0, b1, b2, b3;
                ldmatrix_x4(b0, b1, b2, b3, sK + (kb * 64 + np * 16) * 32 + koff);
#pragma unroll
                for (int m = 0; m < 2; m++) {
#pragma unroll
                    for (int i = 0; i < 4; i++) { s[m][np * 2][i] = 0.f; s[m][np * 2 + 1][i] = 0.f; }
                    mma_f(s[m][np * 2], qa[m], b0, b1);
                    mma_f(s[m][np * 2 + 1], qa[m], b2, b3);
                }
            }
            uint32_t pa[2][4][4];
#pragma unroll
            for (int m = 0; m < 2; m++) {
                float mx0 = s[m][0][0], mx1 = s[m][0][2];
#pragma unroll
                for (int n = 0; n < 8; n++) {
                    mx0 = fmaxf(mx0, fmaxf(s[m][n][0], s[m][n][1]));
                    mx1 = fmaxf(mx1, fmaxf(s[m][n][2], s[m][n][3]));
                }
                mx0 = fmaxf(mx0, __shfl_xor_sync(0xffffffff, mx0, 1)); mx0 = fmaxf(mx0, __shfl_xor_sync(0xffffffff, mx0, 2));
                mx1 = fmaxf(mx1, __shfl_xor_sync(0xffffffff, mx1, 1)); mx1 = fmaxf(mx1, __shfl_xor_sync(0xffffffff, mx1, 2));
                const float mn0 = fmaxf(mrow[m][0], mx0), mn1 = fmaxf(mrow[m][1], mx1);
                const float a0 = ex2a((mrow[m][0] - mn0) * sc), a1 = ex2a((mrow[m][1] - mn1) * sc);
                mrow[m][0] = mn0; mrow[m][1] = mn1;
                const float mb0 = mn0 * sc, mb1 = mn1 * sc;
#pragma unroll
                for (int d = 0; d < 2; d++) { oacc[m][d][0] *= a0; oacc[m][d][1] *= a0; oacc[m][d][2] *= a1; oacc[m][d][3] *= a1; }
                lacc[m][0] *= a0; lacc[m][2] *= a1;
#pragma unroll
                for (int n = 0; n < 8; n++) {
                    float p0 = ex2a(fmaf(s[m][n][0], sc, -mb0)), p1 = ex2a(fmaf(s[m][n][1], sc, -mb0));
                    float p2 = ex2a(fmaf(s[m][n][2], sc, -mb1)), p3 = ex2a(fmaf(s[m][n][3], sc, -mb1));
                    pa[m][n >> 1][(n & 1) * 2 + 0] = pack_bf16(p0, p1);
                    pa[m][n >> 1][(n & 1) * 2 + 1] = pack_bf16(p2, p3);
                }
            }
#pragma unroll
            for (int ks = 0; ks < 4; ks++) {
                uint32_t b0, b1, b2, b3;
                ldmatrix_x4_t(b0, b1, b2, b3, sV + (kb * 64 + ks * 16) * 32 + voff);
#pragma unroll
                for (int m = 0; m < 2; m++) {
                    mma_f(oacc[m][0], pa[m][ks], b0, b1);
                    mma_f(oacc[m][1], pa[m][ks], b2, b3);
                    mma_f(lacc[m], pa[m][ks], ones, ones);
                }
            }
        }
        __syncwarp();
        if (lane == 0) mbar_arrive(bars + 8 * (AA_NST + st));
        if (tid == 0 && t + AA_NST < NT) {
            mbar_wait(bars + 8 * (AA_NST + st), (t / AA_NST) & 1);
            issue(t + AA_NST);
        }
    }
#pragma unroll
    for (int m = 0; m < 2; m++) {
        const float i0 = 1.0f / lacc[m][0], i1 = 1.0f / lacc[m][2];
        bf16* o = p.o + (size_t)(row0 + m * 16 + g8) * 512 + head * 16 + t4 * 2;
#pragma unroll
        for (int d = 0; d < 2; d++) {
            *reinterpret_cast<uint32_t*>(o + d * 8) = pack_bf16(oacc[m][d][0] * i0, oacc[m][d][1] * i0);
            *reinterpret_cast<uint32_t*>(o + 8 * 512 + d * 8) = pack_bf16(oacc[m][d][2] * i1, oacc[m][d][3] * i1);
        }
    }
}

struct AttnBParams {
    CUtensorMap tmQKV;
    CUtensorMap tmKVM;
    CUtensorMap tmO;
    const unsigned int* seg_flags;
    unsigned int seg_target;
    unsigned int* tile_flags;
};
constexpr int AB_WARP_BYTES = 28672;
constexpr int AB_SMEM = 4 * AB_WARP_BYTES + 64;

__global__ void __launch_bounds__(128, 2) attn_b_kernel(const __grid_constant__ AttnBParams p) {
    extern __shared__ __align__(1024) unsigned char smem[];
    const int tid = threadIdx.x, lane = tid & 31, warp = tid >> 5;
    const uint32_t sb = smem_u32(smem) + warp * AB_WARP_BYTES;
    const uint32_t bar = smem_u32(smem) + 4 * AB_WARP_BYTES + warp * 8;
    asm volatile("griddepcontrol.launch_dependents;" ::: "memory");
    const int seg = blockIdx.x >> 3, head = (blockIdx.x & 7) * 4 + warp;
    const int t4 = lane & 3, g8 = lane >> 2;
    const uint32_t sQ = sb, sK = sb + 8192, sV = sb + 16384, sKm = sb + 24576, sVm = sb + 26624;
    if (lane == 0) {
        mbar_init(bar, 1);
        fence_mbar_init();
        if (p.seg_flags) {
            uint32_t n = 0;
            while (ld_acquire_u32(p.seg_flags + seg) < p.seg_target) { if (++n > (1u << 24)) break; __nanosleep(200); }
            fence_proxy_async_all();
        }
        mbar_expect_tx(bar, AB_WARP_BYTES);
#pragma unroll
        for (int h = 0; h < 2; h++) {
            tma_load_3d(sQ + h * 4096, &p.tmQKV, 0, seg * 32, head * 2 + h, bar);
            tma_load_3d(sK + h * 4096, &p.tmQKV, 0, seg * 32, 64 + head * 2 + h, bar);
            tma_load_3d(sV + h * 4096, &p.tmQKV, 0, seg * 32, 128 + head * 2 + h, bar);
            tma_load_3d(sKm + h * 1024, &p.tmKVM, 0, seg * 8, head * 2 + h, bar);
            tma_load_3d(sVm + h * 1024, &p.tmKVM, 0, seg * 8, 64 + head * 2 + h, bar);
        }
    }
    __syncwarp();
    mbar_wait(bar, 0);
    const int lr = lane & 7, lm = lane >> 3;
    float s[2][5][4];
#pragma unroll
    for (int m = 0; m < 2; m++)
#pragma unroll
        for (int n = 0; n < 5; n++)
#pragma unroll
            for (int i = 0; i < 4; i++) s[m][n][i] = 0.f;
#pragma unroll
    for (int kp = 0; kp < 4; kp++) {
        const int hb = kp >> 1, c0 = (kp & 1) * 4;
        uint32_t a[2][2][4];
#pragma unroll
        for (int m = 0; m < 2; m++)
#pragma unroll
            for (int ks = 0; ks < 2; ks++) {
                int row = m * 16 + (lm & 1) * 8 + lr, ch = c0 + ks * 2 + (lm >> 1);
                ldmatrix_x4(a[m][ks][0], a[m][ks][1], a[m][ks][2], a[m][ks][3], sQ + hb * 4096 + row * 128 + ((ch ^ (row & 7)) << 4));
            }
#pragma unroll
        for (int n = 0; n < 5; n++) {
            uint32_t b0, b1, b2, b3;
            int ch = c0 + lm;
            if (n == 0) ldmatrix_x4(b0, b1, b2, b3, sKm + hb * 1024 + lr * 128 + ((ch ^ lr) << 4));
            else { int row = (n - 1) * 8 + lr; ldmatrix_x4(b0, b1, b2, b3, sK + hb * 4096 + row * 128 + ((ch ^ (row & 7)) << 4)); }
#pragma unroll
            for (int m = 0; m < 2; m++) { mma_f(s[m][n], a[m][0], b0, b1); mma_f(s[m][n], a[m][1], b2, b3); }
        }
    }
    const float sc = 0.08838834764831845f * 1.4426950408889634f;
    uint32_t pa[2][3][4];
    float inv[2][2];
#pragma unroll
    for (int m = 0; m < 2; m++) {
        const int r0 = m * 16 + g8, r1 = r0 + 8;
        float mx0 = -3.0e38f, mx1 = -3.0e38f;
#pragma unroll
        for (int n = 0; n < 5; n++) {
            if (n > 0) {
                int j = (n - 1) * 8 + t4 * 2;
                if (j > r0) s[m][n][0] = -3.0e38f;
                if (j + 1 > r0) s[m][n][1] = -3.0e38f;
                if (j > r1) s[m][n][2] = -3.0e38f;
                if (j + 1 > r1) s[m][n][3] = -3.0e38f;
            }
            mx0 = fmaxf(mx0, fmaxf(s[m][n][0], s[m][n][1]));
            mx1 = fmaxf(mx1, fmaxf(s[m][n][2], s[m][n][3]));
        }
        mx0 = fmaxf(mx0, __shfl_xor_sync(0xffffffff, mx0, 1)); mx0 = fmaxf(mx0, __shfl_xor_sync(0xffffffff, mx0, 2));
        mx1 = fmaxf(mx1, __shfl_xor_sync(0xffffffff, mx1, 1)); mx1 = fmaxf(mx1, __shfl_xor_sync(0xffffffff, mx1, 2));
        const float mb0 = mx0 * sc, mb1 = mx1 * sc;
        float l0 = 0.f, l1 = 0.f;
#pragma unroll
        for (int n = 0; n < 5; n++) {
            s[m][n][0] = ex2a(fmaf(s[m][n][0], sc, -mb0)); s[m][n][1] = ex2a(fmaf(s[m][n][1], sc, -mb0));
            s[m][n][2] = ex2a(fmaf(s[m][n][2], sc, -mb1)); s[m][n][3] = ex2a(fmaf(s[m][n][3], sc, -mb1));
            l0 += s[m][n][0] + s[m][n][1]; l1 += s[m][n][2] + s[m][n][3];
        }
        l0 += __shfl_xor_sync(0xffffffff, l0, 1); l0 += __shfl_xor_sync(0xffffffff, l0, 2);
        l1 += __shfl_xor_sync(0xffffffff, l1, 1); l1 += __shfl_xor_sync(0xffffffff, l1, 2);
        inv[m][0] = 1.0f / l0; inv[m][1] = 1.0f / l1;
#pragma unroll
        for (int n = 0; n < 5; n++) {
            pa[m][n >> 1][(n & 1) * 2 + 0] = pack_bf16(s[m][n][0] * inv[m][0], s[m][n][1] * inv[m][0]);
            pa[m][n >> 1][(n & 1) * 2 + 1] = pack_bf16(s[m][n][2] * inv[m][1], s[m][n][3] * inv[m][1]);
        }
        pa[m][2][2] = 0u; pa[m][2][3] = 0u;
    }
    __syncwarp();
#pragma unroll
    for (int dq = 0; dq < 4; dq++) {
        float oc[2][4][4];
#pragma unroll
        for (int m = 0; m < 2; m++)
#pragma unroll
            for (int n = 0; n < 4; n++)
#pragma unroll
                for (int i = 0; i < 4; i++) oc[m][n][i] = 0.f;
        const int hb = dq >> 1, c0 = (dq & 1) * 4;
#pragma unroll
        for (int ks = 0; ks < 3; ks++) {
#pragma unroll
            for (int dp = 0; dp < 2; dp++) {
                int key = ks * 16 + (lm & 1) * 8 + lr, ch = c0 + dp * 2 + (lm >> 1);
                uint32_t addr;
                if (key < 8 || key >= 40) addr = sVm + hb * 1024 + lr * 128 + ((ch ^ lr) << 4);
                else { int row = key - 8; addr = sV + hb * 4096 + row * 128 + ((ch ^ (row & 7)) << 4); }
                uint32_t b0, b1, b2, b3;
                ldmatrix_x4_t(b0, b1, b2, b3, addr);
#pragma unroll
                for (int m = 0; m < 2; m++) { mma_f(oc[m][dp * 2], pa[m][ks], b0, b1); mma_f(oc[m][dp * 2 + 1], pa[m][ks], b2, b3); }
            }
        }
#pragma unroll
        for (int m = 0; m < 2; m++)
#pragma unroll
            for (int dp = 0; dp < 2; dp++) {
                int row = m * 16 + (lm & 1) * 8 + lr, ch = c0 + dp * 2 + (lm >> 1);
                stmatrix_x4(sQ + hb * 4096 + row * 128 + ((ch ^ (row & 7)) << 4),
                            pack_bf16(oc[m][dp * 2][0], oc[m][dp * 2][1]), pack_bf16(oc[m][dp * 2][2], oc[m][dp * 2][3]),
                            pack_bf16(oc[m][dp * 2 + 1][0], oc[m][dp * 2 + 1][1]), pack_bf16(oc[m][dp * 2 + 1][2], oc[m][dp * 2 + 1][3]));
            }
    }
    fence_proxy_async_smem();
    __syncwarp();
    if (lane == 0) {
        tma_store_3d(&p.tmO, sQ, 0, seg * 32, head * 2);
        tma_store_3d(&p.tmO, sQ + 4096, 0, seg * 32, head * 2 + 1);
        bulk_commit();
        bulk_wait_all0();
        fence_proxy_async_all();
        __threadfence();
        atomicAdd(p.tile_flags + (seg >> 2), 1u);
    }
}

struct GemmSParams {
    CUtensorMap tmA;
    CUtensorMap tmB;
    CUtensorMap tmC;
    int n_tiles;
    int kblocks_half;
    int c_col64;
    const unsigned int* tile_flags;
    unsigned int tile_target;
};
constexpr int GS_NST = 5;
constexpr int GS_SMEM = GS_NST * 32768 + 32768 + 256;

__global__ void __launch_bounds__(288, 1) gemm_s_kernel(const __grid_constant__ GemmSParams p) {
    extern __shared__ __align__(1024) unsigned char smem[];
    const uint32_t sS = smem_u32(smem);
    const uint32_t sR = sS + GS_NST * 32768;
    const uint32_t bars = sR + 32768;
    const uint32_t barFull = bars, barEmpty = bars + 8 * GS_NST, barRed = bars + 16 * GS_NST;
    const int warp = __shfl_sync(0xffffffff, threadIdx.x >> 5, 0), lane = threadIdx.x & 31;
    const int tile = blockIdx.x >> 1, kh = blockIdx.x & 1;
    const int mt = tile / p.n_tiles, nt = tile % p.n_tiles;
    if (threadIdx.x == 0) {
        for (int i = 0; i < GS_NST; i++) { mbar_init(barFull + 8 * i, 1); mbar_init(barEmpty + 8 * i, 8); }
        mbar_init(barRed, 1);
        fence_mbar_init();
        mbar_expect_tx(barRed, 32768);
    }
    __syncthreads();
    cluster_sync_all();
    if (warp == 8) {
        if (lane == 0) {
            {
                uint32_t n = 0;
                while (ld_acquire_u32(p.tile_flags + mt) < p.tile_target) { if (++n > (1u << 24)) break; __nanosleep(200); }
                fence_proxy_async_all();
            }
            for (int i = 0; i < p.kblocks_half; i++) {
                int slot = i % GS_NST;
                if (i >= GS_NST) mbar_wait(barEmpty + 8 * slot, ((i / GS_NST) - 1) & 1);
                mbar_expect_tx(barFull + 8 * slot, 32768);
                int kb = kh * p.kblocks_half + i;
                tma_load_3d(sS + slot * 32768, &p.tmA, 0, mt * 128, kb, barFull + 8 * slot);
                tma_load_3d(sS + slot * 32768 + 16384, &p.tmB, 0, kb * 64, nt * 2, barFull + 8 * slot);
            }
        }
    } else {
        const int wg = warp >> 2, wq = warp & 3;
        float acc[64];
        int prev = 0;
        for (int i = 0; i < p.kblocks_half; i++) {
            int slot = i % GS_NST;
            mbar_wait(barFull + 8 * slot, (i / GS_NST) & 1);
            wg_fence();
            uint64_t da = make_desc(sS + slot * 32768 + wg * 8192, 16, 1024);
            uint64_t db = make_desc(sS + slot * 32768 + 16384, 8192, 1024);
#pragma unroll
            for (int kk = 0; kk < 4; kk++)
                wgmma_m64n128k16_ss_tb(acc, da + (uint64_t)(kk * 2), db + (uint64_t)(kk * 128), (i | kk) != 0);
            wg_commit();
            if (i > 0) { wg_wait<1>(); if (lane == 0) mbar_arrive(barEmpty + 8 * prev); }
            prev = slot;
        }
        wg_wait<0>();
        const uint32_t peer = kh ^ 1;
        const uint32_t rbuf = mapa_u32(sR, peer), rbar = mapa_u32(barRed, peer);
        const int tw = threadIdx.x;
#pragma unroll
        for (int j = 0; j < 8; j++) {
            float a[4];
#pragma unroll
            for (int i = 0; i < 4; i++) a[i] = kh == 0 ? acc[(8 + j) * 4 + i] : acc[j * 4 + i];
            st_async_v4(rbuf + (j * 256 + tw) * 16, __float_as_uint(a[0]), __float_as_uint(a[1]), __float_as_uint(a[2]), __float_as_uint(a[3]), rbar);
        }
        mbar_wait(barRed, 0);
        named_bar_sync(1, 256);
        const uint32_t stage = sS + wg * 8192;
        const int mrow = wq * 16 + (lane & 7) + ((lane >> 3) & 1) * 8, mcolh = lane >> 4;
#pragma unroll
        for (int c = 0; c < 4; c++) {
            uint32_t r[4];
#pragma unroll
            for (int e = 0; e < 2; e++) {
                int j = c * 2 + e;
                float4 v;
                asm volatile("ld.shared.v4.f32 {%0,%1,%2,%3}, [%4];" : "=f"(v.x), "=f"(v.y), "=f"(v.z), "=f"(v.w) : "r"(sR + (j * 256 + tw) * 16) : "memory");
                float a[4];
#pragma unroll
                for (int i = 0; i < 4; i++) a[i] = kh == 0 ? acc[j * 4 + i] : acc[(8 + j) * 4 + i];
                r[e * 2 + 0] = pack_bf16(a[0] + v.x, a[1] + v.y);
                r[e * 2 + 1] = pack_bf16(a[2] + v.z, a[3] + v.w);
            }
            int chunk = (c * 2 + mcolh) ^ (mrow & 7);
            stmatrix_x4(stage + mrow * 128 + chunk * 16, r[0], r[1], r[2], r[3]);
        }
        fence_proxy_async_smem();
        named_bar_sync(2 + wg, 128);
        if ((threadIdx.x & 127) == 0) {
            tma_store_3d(&p.tmC, stage, 0, mt * 128 + wg * 64, p.c_col64 + nt * 2 + kh);
            bulk_commit();
            bulk_wait_read0();
        }
    }
    __syncthreads();
    cluster_sync_all();
}

typedef CUresult (*PFN_encodeTiled)(CUtensorMap*, CUtensorMapDataType, cuuint32_t, void*, const cuuint64_t*, const cuuint64_t*,
                                    const cuuint32_t*, const cuuint32_t*, CUtensorMapInterleave, CUtensorMapSwizzle,
                                    CUtensorMapL2promotion, CUtensorMapFloatOOBfill);
static PFN_encodeTiled g_encode = nullptr;
static void init_encode() {
    if (g_encode) return;
    void* fn = nullptr;
    cudaDriverEntryPointQueryResult st;
    cudaGetDriverEntryPoint("cuTensorMapEncodeTiled", &fn, cudaEnableDefault, &st);
    g_encode = (PFN_encodeTiled)fn;
}
static CUtensorMap make_tmap_3d64(const void* ptr, uint64_t rows, uint64_t cols, uint64_t ld, uint32_t box_rows, uint32_t box_c64) {
    CUtensorMap tm;
    cuuint64_t dims[3] = {64, rows, cols / 64};
    cuuint64_t strides[2] = {ld * 2, 128};
    cuuint32_t box[3] = {64, box_rows, box_c64};
    cuuint32_t es[3] = {1, 1, 1};
    g_encode(&tm, CU_TENSOR_MAP_DATA_TYPE_BFLOAT16, 3, (void*)ptr, dims, strides, box, es, CU_TENSOR_MAP_INTERLEAVE_NONE,
             CU_TENSOR_MAP_SWIZZLE_128B, CU_TENSOR_MAP_L2_PROMOTION_L2_128B, CU_TENSOR_MAP_FLOAT_OOB_FILL_NONE);
    return tm;
}

__device__ __align__(1024) bf16 g_qkvA[2048 * 1536];
__device__ __align__(1024) bf16 g_oA[2048 * 512];
__device__ __align__(1024) bf16 g_qkvB[2048 * 12288];
__device__ __align__(1024) bf16 g_kvmem[64 * 8 * 8192];
__device__ __align__(1024) bf16 g_oB[2048 * 4096];
__device__ __align__(1024) float g_part[2 * 64 * 256];
__device__ __align__(128) unsigned int g_flags[192];

__global__ void cleanup_kernel() {
    const int i = blockIdx.x * blockDim.x + threadIdx.x;
    const int n = gridDim.x * blockDim.x;
    uint4 z = make_uint4(0, 0, 0, 0);
    for (int k = i; k < 2 * 64 * 64; k += n) reinterpret_cast<uint4*>(g_part)[k] = z;
    if (i < 192) g_flags[i] = 0u;
}

template <typename T> static T* sym_addr(T& sym) { void* p = nullptr; cudaGetSymbolAddress(&p, sym); return (T*)p; }

extern "C" void kernel_launch(void* const* d_in, const int* in_sizes, int n_in, void* d_out, int out_size) {
    const bf16* A_x = (const bf16*)d_in[0];
    const bf16* A_wqkv = (const bf16*)d_in[1];
    const bf16* A_wo = (const bf16*)d_in[2];
    const bf16* B_x = (const bf16*)d_in[3];
    const bf16* B_mem0 = (const bf16*)d_in[4];
    const bf16* B_Wq = (const bf16*)d_in[5];
    const bf16* B_Wk = (const bf16*)d_in[6];
    const bf16* B_Wv = (const bf16*)d_in[7];
    const bf16* B_Wo = (const bf16*)d_in[8];
    bf16* out = (bf16*)d_out;

    static bool inited = false;
    static cudaStream_t s1;
    static cudaEvent_t e_kv, e_s1, e_ch;
    if (!inited) {
        init_encode();
        cudaFuncSetAttribute(gemm_w_kernel, cudaFuncAttributeMaxDynamicSharedMemorySize, GW_SMEM);
        cudaFuncSetAttribute(gemm_s_kernel, cudaFuncAttributeMaxDynamicSharedMemorySize, GS_SMEM);
        cudaFuncSetAttribute(chain_kernel, cudaFuncAttributeMaxDynamicSharedMemorySize, CH_SMEM);
        cudaFuncSetAttribute(chain_kernel, cudaFuncAttributeNonPortableClusterSizeAllowed, 1);
        cudaFuncSetAttribute(attn_a_kernel, cudaFuncAttributeMaxDynamicSharedMemorySize, AA_SMEM);
        cudaFuncSetAttribute(attn_b_kernel, cudaFuncAttributeMaxDynamicSharedMemorySize, AB_SMEM);
        cudaStreamCreateWithFlags(&s1, cudaStreamNonBlocking);
        cudaEventCreateWithFlags(&e_kv, cudaEventDisableTiming);
        cudaEventCreateWithFlags(&e_s1, cudaEventDisableTiming);
        cudaEventCreateWithFlags(&e_ch, cudaEventDisableTiming);
        inited = true;
    }
    void *qkvA, *oA, *qkvB, *kvmem, *oB, *part, *membuf, *flags;
    cudaGetSymbolAddress(&qkvA, g_qkvA); cudaGetSymbolAddress(&oA, g_oA); cudaGetSymbolAddress(&qkvB, g_qkvB);
    cudaGetSymbolAddress(&kvmem, g_kvmem); cudaGetSymbolAddress(&oB, g_oB); cudaGetSymbolAddress(&part, g_part);
    membuf = nullptr; cudaGetSymbolAddress(&flags, g_flags);
    cudaStream_t s0 = cudaStreamPerThread;

    cudaEventRecord(e_kv, s0);
    cudaStreamWaitEvent(s1, e_kv, 0);
    ChainParams pc;
    pc.tmW[0] = make_tmap_3d64(B_Wq, 512, 4096, 4096, 256, 1);
    pc.tmW[1] = make_tmap_3d64(B_Wk, 512, 4096, 4096, 256, 1);
    pc.tmW[2] = make_tmap_3d64(B_Wv, 512, 4096, 4096, 256, 1);
    pc.tmWo = make_tmap_3d64(B_Wo, 4096, 512, 512, 128, 1);
    pc.tmKV = make_tmap_3d64(qkvB, 2048, 12288, 12288, 32, 1);
    pc.mem0 = B_mem0; pc.kvmem = (bf16*)kvmem; pc.part = (float*)part; pc.membuf = (uint4*)membuf;
    pc.flags = (const unsigned int*)flags; pc.flag_target = 128; pc.dbg = nullptr; pc.seg_flags = (unsigned int*)flags + 64;
    {
        cudaLaunchConfig_t cfg = {};
        cfg.gridDim = dim3(64); cfg.blockDim = dim3(384); cfg.dynamicSmemBytes = CH_SMEM; cfg.stream = s1;
        cudaLaunchAttribute at[2];
        at[0].id = cudaLaunchAttributeClusterDimension; at[0].val.clusterDim.x = 16; at[0].val.clusterDim.y = 1; at[0].val.clusterDim.z = 1;
        cfg.attrs = at; cfg.numAttrs = 1;
        cudaLaunchKernelEx(&cfg, chain_kernel, pc);
    }

    cudaEventRecord(e_ch, s1);
    GemmWParams pkv;
    pkv.tmA = make_tmap_3d64(B_x, 2048, 512, 512, 128, 1);
    pkv.tmB[0] = make_tmap_3d64(B_Wk, 512, 4096, 4096, 64, 2);
    pkv.tmB[1] = make_tmap_3d64(B_Wv, 512, 4096, 4096, 64, 2);
    pkv.tmB[2] = make_tmap_3d64(B_Wq, 512, 4096, 4096, 64, 2);
    pkv.tmC = make_tmap_3d64(qkvB, 2048, 12288, 12288, 128, 1);
    pkv.ntiles_per_mat = 32; pkv.c_col64[0] = 64; pkv.c_col64[1] = 128; pkv.c_col64[2] = 0;
    pkv.m_splits = 1; pkv.mtiles_per_cta = 16; pkv.flag_mats = 2; pkv.flags = (unsigned int*)flags;
    {
        cudaLaunchConfig_t cfg = {};
        cfg.gridDim = dim3(64); cfg.blockDim = dim3(384); cfg.dynamicSmemBytes = GW_SMEM; cfg.stream = s1;
        cudaLaunchAttribute at[1];
        at[0].id = cudaLaunchAttributeProgrammaticStreamSerialization; at[0].val.programmaticStreamSerializationAllowed = 1;
        cfg.attrs = at; cfg.numAttrs = 1;
        cudaLaunchKernelEx(&cfg, gemm_w_kernel, pkv);
    }

    GemmWParams pq = pkv;
    pq.tmB[0] = pkv.tmB[2]; pq.c_col64[0] = 0; pq.m_splits = 2; pq.mtiles_per_cta = 8; pq.flag_mats = 0; pq.flags = nullptr;
    gemm_w_kernel<<<64, 384, GW_SMEM, s1>>>(pq);

    GemmWParams p1;
    p1.tmA = make_tmap_3d64(A_x, 2048, 512, 512, 128, 1);
    p1.tmB[0] = make_tmap_3d64(A_wqkv, 512, 1536, 1536, 64, 2); p1.tmB[1] = p1.tmB[0]; p1.tmB[2] = p1.tmB[0];
    p1.tmC = make_tmap_3d64(qkvA, 2048, 1536, 1536, 128, 1);
    p1.ntiles_per_mat = 12; p1.c_col64[0] = p1.c_col64[1] = p1.c_col64[2] = 0;
    p1.m_splits = 4; p1.mtiles_per_cta = 4; p1.flag_mats = 0; p1.flags = nullptr;
    gemm_w_kernel<<<48, 384, GW_SMEM, s1>>>(p1);

    AttnAParams pa;
    {
        cuuint64_t dims[2] = {1536, 2048}; cuuint64_t strides[1] = {3072}; cuuint32_t box[2] = {16, AA_KT}; cuuint32_t es[2] = {1, 1};
        g_encode(&pa.tmKV, CU_TENSOR_MAP_DATA_TYPE_BFLOAT16, 2, qkvA, dims, strides, box, es, CU_TENSOR_MAP_INTERLEAVE_NONE,
                 CU_TENSOR_MAP_SWIZZLE_32B, CU_TENSOR_MAP_L2_PROMOTION_L2_128B, CU_TENSOR_MAP_FLOAT_OOB_FILL_NONE);
    }
    pa.qkv = (const bf16*)qkvA; pa.o = (bf16*)oA;
    attn_a_kernel<<<256, 256, AA_SMEM, s1>>>(pa);

    GemmWParams p2;
    p2.tmA = make_tmap_3d64(oA, 2048, 512, 512, 128, 1);
    p2.tmB[0] = make_tmap_3d64(A_wo, 512, 512, 512, 64, 2); p2.tmB[1] = p2.tmB[0]; p2.tmB[2] = p2.tmB[0];
    p2.tmC = make_tmap_3d64(out, 2048, 1024, 1024, 128, 1);
    p2.ntiles_per_mat = 4; p2.c_col64[0] = p2.c_col64[1] = p2.c_col64[2] = 0;
    p2.m_splits = 16; p2.mtiles_per_cta = 1; p2.flag_mats = 0; p2.flags = nullptr;
    gemm_w_kernel<<<64, 384, GW_SMEM, s1>>>(p2);

    AttnBParams pb;
    pb.tmQKV = make_tmap_3d64(qkvB, 2048, 12288, 12288, 32, 1);
    pb.tmKVM = make_tmap_3d64(kvmem, 512, 8192, 8192, 8, 1);
    pb.tmO = make_tmap_3d64(oB, 2048, 4096, 4096, 32, 1);
    pb.seg_flags = (const unsigned int*)flags + 64; pb.seg_target = 256; pb.tile_flags = (unsigned int*)flags + 128;
    attn_b_kernel<<<512, 128, AB_SMEM, s1>>>(pb);

    GemmSParams p4;
    p4.tmA = make_tmap_3d64(oB, 2048, 4096, 4096, 128, 1);
    p4.tmB = make_tmap_3d64(B_Wo, 4096, 512, 512, 64, 2);
    p4.tmC = make_tmap_3d64(out, 2048, 1024, 1024, 64, 1);
    p4.n_tiles = 4; p4.kblocks_half = 32; p4.c_col64 = 8;
    p4.tile_flags = (const unsigned int*)flags + 128; p4.tile_target = 128;
    {
        cudaLaunchConfig_t cfg = {};
        cfg.gridDim = dim3(128); cfg.blockDim = dim3(288); cfg.dynamicSmemBytes = GS_SMEM; cfg.stream = s1;
        cudaLaunchAttribute at[2];
        at[0].id = cudaLaunchAttributeClusterDimension; at[0].val.clusterDim.x = 2; at[0].val.clusterDim.y = 1; at[0].val.clusterDim.z = 1;
        at[1].id = cudaLaunchAttributeProgrammaticStreamSerialization; at[1].val.programmaticStreamSerializationAllowed = 1;
        cfg.attrs = at; cfg.numAttrs = 2;
        cudaLaunchKernelEx(&cfg, gemm_s_kernel, p4);
    }
    cudaEventRecord(e_s1, s1);
    cudaStreamWaitEvent(s0, e_s1, 0);
    cudaStreamWaitEvent(s0, e_ch, 0);
    cleanup_kernel<<<64, 256, 0, s0>>>();
}
```

```cpp
#include <cuda_runtime.h>
#include <cuda_bf16.h>
#include <cuda.h>
#include <stdint.h>

typedef __nv_bfloat16 bf16;

__device__ __forceinline__ uint32_t smem_u32(const void* p) { return (uint32_t)__cvta_generic_to_shared(p); }
__device__ __forceinline__ void mbar_init(uint32_t bar, uint32_t cnt) {
    asm volatile("mbarrier.init.shared::cta.b64 [%0], %1;" :: "r"(bar), "r"(cnt) : "memory");
}
__device__ __forceinline__ void mbar_expect_tx(uint32_t bar, uint32_t bytes) {
    asm volatile("mbarrier.arrive.expect_tx.shared::cta.b64 _, [%0], %1;" :: "r"(bar), "r"(bytes) : "memory");
}
__device__ __forceinline__ void mbar_arrive(uint32_t bar) {
    asm volatile("mbarrier.arrive.shared::cta.b64 _, [%0];" :: "r"(bar) : "memory");
}
__device__ __forceinline__ bool mbar_try_wait(uint32_t bar, uint32_t parity) {
    uint32_t ok;
    asm volatile("{\n.reg .pred p;\nmbarrier.try_wait.parity.shared::cta.b64 p, [%1], %2;\nselp.u32 %0, 1, 0, p;\n}"
                 : "=r"(ok) : "r"(bar), "r"(parity) : "memory");
    return ok != 0;
}
__device__ __forceinline__ void mbar_wait(uint32_t bar, uint32_t parity) {
    uint32_t n = 0;
    while (!mbar_try_wait(bar, parity)) { if (++n > (1u << 20)) break; }
}
__device__ __forceinline__ void fence_proxy_async_smem() { asm volatile("fence.proxy.async.shared::cta;" ::: "memory"); }
__device__ __forceinline__ void fence_proxy_async_all() { asm volatile("fence.proxy.async;" ::: "memory"); }
__device__ __forceinline__ void fence_mbar_init() { asm volatile("fence.mbarrier_init.release.cluster;" ::: "memory"); }

__device__ __forceinline__ void tma_load_3d(uint32_t dst, const CUtensorMap* tm, int c0, int c1, int c2, uint32_t bar) {
    asm volatile("cp.async.bulk.tensor.3d.shared::cluster.global.mbarrier::complete_tx::bytes [%0], [%1, {%3, %4, %5}], [%2];"
                 :: "r"(dst), "l"(tm), "r"(bar), "r"(c0), "r"(c1), "r"(c2) : "memory");
}
__device__ __forceinline__ void tma_load_2d(uint32_t dst, const CUtensorMap* tm, int c0, int c1, uint32_t bar) {
    asm volatile("cp.async.bulk.tensor.2d.shared::cluster.global.mbarrier::complete_tx::bytes [%0], [%1, {%3, %4}], [%2];"
                 :: "r"(dst), "l"(tm), "r"(bar), "r"(c0), "r"(c1) : "memory");
}
__device__ __forceinline__ void tma_store_3d(const CUtensorMap* tm, uint32_t src, int c0, int c1, int c2) {
    asm volatile("cp.async.bulk.tensor.3d.global.shared::cta.bulk_group [%0, {%2, %3, %4}], [%1];"
                 :: "l"(tm), "r"(src), "r"(c0), "r"(c1), "r"(c2) : "memory");
}
__device__ __forceinline__ void bulk_commit() { asm volatile("cp.async.bulk.commit_group;" ::: "memory"); }
__device__ __forceinline__ void bulk_wait_read0() { asm volatile("cp.async.bulk.wait_group.read 0;" ::: "memory"); }
__device__ __forceinline__ void bulk_wait_all0() { asm volatile("cp.async.bulk.wait_group 0;" ::: "memory"); }
__device__ __forceinline__ void prefetch_tmap(const CUtensorMap* tm) {
    asm volatile("prefetch.tensormap [%0];" :: "l"(tm) : "memory");
}

__device__ __forceinline__ void wg_fence() { asm volatile("wgmma.fence.sync.aligned;" ::: "memory"); }
__device__ __forceinline__ void wg_commit() { asm volatile("wgmma.commit_group.sync.aligned;" ::: "memory"); }
template <int N> __device__ __forceinline__ void wg_wait() { asm volatile("wgmma.wait_group.sync.aligned %0;" :: "n"(N) : "memory"); }

__device__ __forceinline__ void named_bar_sync(int id, int nthreads) {
    asm volatile("bar.sync %0, %1;" :: "r"(id), "r"(nthreads) : "memory");
}
__device__ __forceinline__ void named_bar_arrive(int id, int nthreads) {
    asm volatile("bar.arrive %0, %1;" :: "r"(id), "r"(nthreads) : "memory");
}

__device__ __forceinline__ uint64_t make_desc(uint32_t saddr, uint32_t lbo_bytes, uint32_t sbo_bytes) {
    return (uint64_t)((saddr & 0x3FFFF) >> 4) | ((uint64_t)(lbo_bytes >> 4) << 16) | ((uint64_t)(sbo_bytes >> 4) << 32) | ((uint64_t)1 << 62);
}

__device__ __forceinline__ uint32_t pack_bf16(float lo, float hi) {
    uint32_t r;
    asm("cvt.rn.bf16x2.f32 %0, %1, %2;" : "=r"(r) : "f"(hi), "f"(lo));
    return r;
}
__device__ __forceinline__ void stmatrix_x4(uint32_t addr, uint32_t r0, uint32_t r1, uint32_t r2, uint32_t r3) {
    asm volatile("stmatrix.sync.aligned.m8n8.x4.shared.b16 [%0], {%1,%2,%3,%4};" :: "r"(addr), "r"(r0), "r"(r1), "r"(r2), "r"(r3) : "memory");
}
__device__ __forceinline__ void ldmatrix_x4(uint32_t& r0, uint32_t& r1, uint32_t& r2, uint32_t& r3, uint32_t addr) {
    asm volatile("ldmatrix.sync.aligned.m8n8.x4.shared.b16 {%0,%1,%2,%3}, [%4];" : "=r"(r0), "=r"(r1), "=r"(r2), "=r"(r3) : "r"(addr) : "memory");
}
__device__ __forceinline__ void ldmatrix_x4_t(uint32_t& r0, uint32_t& r1, uint32_t& r2, uint32_t& r3, uint32_t addr) {
    asm volatile("ldmatrix.sync.aligned.m8n8.x4.trans.shared.b16 {%0,%1,%2,%3}, [%4];" : "=r"(r0), "=r"(r1), "=r"(r2), "=r"(r3) : "r"(addr) : "memory");
}
__device__ __forceinline__ void ldmatrix_x2(uint32_t& r0, uint32_t& r1, uint32_t addr) {
    asm volatile("ldmatrix.sync.aligned.m8n8.x2.shared.b16 {%0,%1}, [%2];" : "=r"(r0), "=r"(r1) : "r"(addr) : "memory");
}
__device__ __forceinline__ void ldmatrix_x2_t(uint32_t& r0, uint32_t& r1, uint32_t addr) {
    asm volatile("ldmatrix.sync.aligned.m8n8.x2.trans.shared.b16 {%0,%1}, [%2];" : "=r"(r0), "=r"(r1) : "r"(addr) : "memory");
}
__device__ __forceinline__ void mma16816(float* c, const uint32_t* a, uint32_t b0, uint32_t b1) {
    asm volatile("mma.sync.aligned.m16n8k16.row.col.f32.bf16.bf16.f32 {%0,%1,%2,%3}, {%4,%5,%6,%7}, {%8,%9}, {%0,%1,%2,%3};"
                 : "+f"(c[0]), "+f"(c[1]), "+f"(c[2]), "+f"(c[3]) : "r"(a[0]), "r"(a[1]), "r"(a[2]), "r"(a[3]), "r"(b0), "r"(b1));
}

__device__ __forceinline__ void wgmma_m64n128k16_ss_tb(float* d, uint64_t da, uint64_t db, int scale_d) {
    asm volatile(
        "{\n.reg .pred p;\nsetp.ne.b32 p, %66, 0;\n"
        "wgmma.mma_async.sync.aligned.m64n128k16.f32.bf16.bf16 "
        "{%0,%1,%2,%3,%4,%5,%6,%7,%8,%9,%10,%11,%12,%13,%14,%15,"
        "%16,%17,%18,%19,%20,%21,%22,%23,%24,%25,%26,%27,%28,%29,%30,%31,"
        "%32,%33,%34,%35,%36,%37,%38,%39,%40,%41,%42,%43,%44,%45,%46,%47,"
        "%48,%49,%50,%51,%52,%53,%54,%55,%56,%57,%58,%59,%60,%61,%62,%63},"
        " %64, %65, p, 1, 1, 0, 1;\n}\n"
        : "+f"(d[0]), "+f"(d[1]), "+f"(d[2]), "+f"(d[3]), "+f"(d[4]), "+f"(d[5]), "+f"(d[6]), "+f"(d[7]),
          "+f"(d[8]), "+f"(d[9]), "+f"(d[10]), "+f"(d[11]), "+f"(d[12]), "+f"(d[13]), "+f"(d[14]), "+f"(d[15]),
          "+f"(d[16]), "+f"(d[17]), "+f"(d[18]), "+f"(d[19]), "+f"(d[20]), "+f"(d[21]), "+f"(d[22]), "+f"(d[23]),
          "+f"(d[24]), "+f"(d[25]), "+f"(d[26]), "+f"(d[27]), "+f"(d[28]), "+f"(d[29]), "+f"(d[30]), "+f"(d[31]),
          "+f"(d[32]), "+f"(d[33]), "+f"(d[34]), "+f"(d[35]), "+f"(d[36]), "+f"(d[37]), "+f"(d[38]), "+f"(d[39]),
          "+f"(d[40]), "+f"(d[41]), "+f"(d[42]), "+f"(d[43]), "+f"(d[44]), "+f"(d[45]), "+f"(d[46]), "+f"(d[47]),
          "+f"(d[48]), "+f"(d[49]), "+f"(d[50]), "+f"(d[51]), "+f"(d[52]), "+f"(d[53]), "+f"(d[54]), "+f"(d[55]),
          "+f"(d[56]), "+f"(d[57]), "+f"(d[58]), "+f"(d[59]), "+f"(d[60]), "+f"(d[61]), "+f"(d[62]), "+f"(d[63])
        : "l"(da), "l"(db), "r"(scale_d));
}

__device__ __forceinline__ void wgmma_m64n128k16_rs(float* d, const uint32_t* a, uint64_t db, int scale_d) {
    asm volatile(
        "{\n.reg .pred p;\nsetp.ne.b32 p, %69, 0;\n"
        "wgmma.mma_async.sync.aligned.m64n128k16.f32.bf16.bf16 "
        "{%0,%1,%2,%3,%4,%5,%6,%7,%8,%9,%10,%11,%12,%13,%14,%15,"
        "%16,%17,%18,%19,%20,%21,%22,%23,%24,%25,%26,%27,%28,%29,%30,%31,"
        "%32,%33,%34,%35,%36,%37,%38,%39,%40,%41,%42,%43,%44,%45,%46,%47,"
        "%48,%49,%50,%51,%52,%53,%54,%55,%56,%57,%58,%59,%60,%61,%62,%63},"
        " {%64,%65,%66,%67}, %68, p, 1, 1, 0;\n}\n"
        : "+f"(d[0]), "+f"(d[1]), "+f"(d[2]), "+f"(d[3]), "+f"(d[4]), "+f"(d[5]), "+f"(d[6]), "+f"(d[7]),
          "+f"(d[8]), "+f"(d[9]), "+f"(d[10]), "+f"(d[11]), "+f"(d[12]), "+f"(d[13]), "+f"(d[14]), "+f"(d[15]),
          "+f"(d[16]), "+f"(d[17]), "+f"(d[18]), "+f"(d[19]), "+f"(d[20]), "+f"(d[21]), "+f"(d[22]), "+f"(d[23]),
          "+f"(d[24]), "+f"(d[25]), "+f"(d[26]), "+f"(d[27]), "+f"(d[28]), "+f"(d[29]), "+f"(d[30]), "+f"(d[31]),
          "+f"(d[32]), "+f"(d[33]), "+f"(d[34]), "+f"(d[35]), "+f"(d[36]), "+f"(d[37]), "+f"(d[38]), "+f"(d[39]),
          "+f"(d[40]), "+f"(d[41]), "+f"(d[42]), "+f"(d[43]), "+f"(d[44]), "+f"(d[45]), "+f"(d[46]), "+f"(d[47]),
          "+f"(d[48]), "+f"(d[49]), "+f"(d[50]), "+f"(d[51]), "+f"(d[52]), "+f"(d[53]), "+f"(d[54]), "+f"(d[55]),
          "+f"(d[56]), "+f"(d[57]), "+f"(d[58]), "+f"(d[59]), "+f"(d[60]), "+f"(d[61]), "+f"(d[62]), "+f"(d[63])
        : "r"(a[0]), "r"(a[1]), "r"(a[2]), "r"(a[3]), "l"(db), "r"(scale_d));
}
__device__ __forceinline__ void stmatrix_x4_t(uint32_t addr, uint32_t r0, uint32_t r1, uint32_t r2, uint32_t r3) {
    asm volatile("stmatrix.sync.aligned.m8n8.x4.trans.shared.b16 [%0], {%1,%2,%3,%4};" :: "r"(addr), "r"(r0), "r"(r1), "r"(r2), "r"(r3) : "memory");
}
template <int R> __device__ __forceinline__ void reg_alloc() { asm volatile("setmaxnreg.inc.sync.aligned.u32 %0;" :: "n"(R)); }
template <int R> __device__ __forceinline__ void reg_dealloc() { asm volatile("setmaxnreg.dec.sync.aligned.u32 %0;" :: "n"(R)); }

struct GemmWParams {
    CUtensorMap tmA;
    CUtensorMap tmB[3];
    CUtensorMap tmC;
    int ntiles_per_mat;
    int c_col64[3];
    int m_splits;
    int mtiles_per_cta;
    int flag_mats;
    unsigned int* flags;
};

constexpr int GW_NST = 11;
constexpr int GW_SMEM = GW_NST * 16384 + 32768 + 256;

__global__ void __launch_bounds__(384, 1) gemm_w_kernel(const __grid_constant__ GemmWParams p) {
    extern __shared__ __align__(1024) unsigned char smem[];
    const uint32_t sA = smem_u32(smem);
    const uint32_t sOut = sA + GW_NST * 16384;
    const uint32_t bars = sOut + 32768;
    const uint32_t barFull = bars, barEmpty = bars + 8 * GW_NST;
    const int warp = __shfl_sync(0xffffffff, threadIdx.x >> 5, 0), lane = threadIdx.x & 31;

    const int gnt = blockIdx.x / p.m_splits;
    const int ms = blockIdx.x % p.m_splits;
    const int mat = gnt / p.ntiles_per_mat;
    const int nt = gnt % p.ntiles_per_mat;
    const int tile0 = ms * p.mtiles_per_cta;
    const int ntl = p.mtiles_per_cta;

    if (threadIdx.x == 0) {
        for (int i = 0; i < GW_NST; i++) { mbar_init(barFull + 8 * i, 1); mbar_init(barEmpty + 8 * i, 8); }
        fence_mbar_init();
    }
    __syncthreads();

    const int wgi = __shfl_sync(0xffffffff, threadIdx.x >> 7, 0);
    if (wgi == 0) {
        reg_dealloc<40>();
        if (warp == 0 && lane == 0) {
            const CUtensorMap* tmB = &p.tmB[mat];
            const int total = 8 + ntl * 8;
            for (int idx = 0; idx < total; idx++) {
                int slot = idx % GW_NST;
                if (idx >= GW_NST) mbar_wait(barEmpty + 8 * slot, ((idx / GW_NST) - 1) & 1);
                mbar_expect_tx(barFull + 8 * slot, 16384);
                if (idx < 8) tma_load_3d(sA + slot * 16384, tmB, 0, idx * 64, nt * 2, barFull + 8 * slot);
                else {
                    int t = (idx - 8) >> 3, j = (idx - 8) & 7;
                    tma_load_3d(sA + slot * 16384, &p.tmA, 0, (tile0 + t) * 128, j, barFull + 8 * slot);
                }
            }
        }
    } else {
        reg_alloc<232>();
        const int wg = (warp >> 2) - 1, wq = warp & 3;
        uint32_t w[32][4];
        float acc[64];
        {
            const int krow = (lane & 7) + ((lane >> 4) & 1) * 8;
            const int chunk = wq * 2 + ((lane >> 3) & 1);
#pragma unroll
            for (int kb = 0; kb < 8; kb++) {
                mbar_wait(barFull + 8 * kb, 0);
#pragma unroll
                for (int kk = 0; kk < 4; kk++) {
                    int r = kk * 16 + krow;
                    uint32_t addr = sA + kb * 16384 + wg * 8192 + r * 128 + ((chunk ^ (r & 7)) << 4);
                    ldmatrix_x4_t(w[kb * 4 + kk][0], w[kb * 4 + kk][1], w[kb * 4 + kk][2], w[kb * 4 + kk][3], addr);
                }
                __syncwarp();
                if (lane == 0) mbar_arrive(barEmpty + 8 * kb);
            }
        }
        const bool do_flag = (p.flags != nullptr) && (mat < p.flag_mats);
        const int tid_wg = threadIdx.x & 127;
        int pend_tile = -1;
        int idx = 8;
        for (int t = 0; t < ntl; t++) {
            int prev_slot = 0;
            if (wg == 0) { if (t > 0) named_bar_sync(3, 256); }
            else named_bar_sync(4, 256);
#pragma unroll
            for (int j = 0; j < 8; j++, idx++) {
                int slot = idx % GW_NST;
                mbar_wait(barFull + 8 * slot, (idx / GW_NST) & 1);
                wg_fence();
                uint64_t db = make_desc(sA + slot * 16384, 16, 1024);
#pragma unroll
                for (int kk = 0; kk < 4; kk++)
                    wgmma_m64n128k16_rs(acc, w[j * 4 + kk], db + (uint64_t)(kk * 2), (j | kk) != 0);
                wg_commit();
                if (j == 7) {
                    if (wg == 0) named_bar_arrive(4, 256);
                    else if (t + 1 < ntl) named_bar_arrive(3, 256);
                }
                if (j > 0) {
                    wg_wait<1>();
                    if (lane == 0) mbar_arrive(barEmpty + 8 * prev_slot);
                }
                prev_slot = slot;
            }
            wg_wait<0>();
            if (lane == 0) mbar_arrive(barEmpty + 8 * prev_slot);
            if (tid_wg == 0 && pend_tile >= 0) {
                if (do_flag) {
                    bulk_wait_all0();
                    fence_proxy_async_all();
                    __threadfence();
                    atomicAdd(p.flags + pend_tile, 1u);
                } else bulk_wait_read0();
            }
            named_bar_sync(1 + wg, 128);
            const uint32_t sbase = sOut + wg * 16384;
            const int mid = lane >> 3;
            const int chunk = wq * 2 + (mid & 1);
#pragma unroll
            for (int nb = 0; nb < 8; nb++) {
                const int a0 = nb * 8;
                uint32_t r0 = pack_bf16(acc[a0 + 0], acc[a0 + 1]);
                uint32_t r1 = pack_bf16(acc[a0 + 2], acc[a0 + 3]);
                uint32_t r2 = pack_bf16(acc[a0 + 4], acc[a0 + 5]);
                uint32_t r3 = pack_bf16(acc[a0 + 6], acc[a0 + 7]);
                int tok = nb * 16 + (mid >> 1) * 8 + (lane & 7);
                stmatrix_x4_t(sbase + tok * 128 + ((chunk ^ (tok & 7)) << 4), r0, r1, r2, r3);
            }
            fence_proxy_async_smem();
            named_bar_sync(1 + wg, 128);
            if (tid_wg == 0) {
                tma_store_3d(&p.tmC, sbase, 0, (tile0 + t) * 128, p.c_col64[mat] + nt * 2 + wg);
                bulk_commit();
            }
            pend_tile = tile0 + t;
        }
        if (pend_tile >= 0 && tid_wg == 0) {
            bulk_wait_all0();
            if (do_flag) {
                fence_proxy_async_all();
                __threadfence();
                atomicAdd(p.flags + pend_tile, 1u);
            }
        }
    }
}

#define PACE 0
#define NSTEPS 64
#define POLL_B 1
#define POLL_R 1
struct ChainParams {
    CUtensorMap tmW[3];
    CUtensorMap tmWo;
    CUtensorMap tmKV;
    const bf16* mem0;
    bf16* kvmem;
    float* part;
    uint4* membuf;
    const unsigned int* flags;
    unsigned int flag_target;
    unsigned int* seg_flags;
    long long* dbg;
};

constexpr int CH_MEM_STRIDE = 1040;
constexpr int CH_Q_STRIDE = 144;
constexpr int CH_O_STRIDE = 272;
constexpr int CH_NKV = 4;
constexpr int CH_KV_BYTES = 15360;
constexpr int CH_OFF_WO = 0;
constexpr int CH_OFF_WV = 65536;
constexpr int CH_OFF_KV = 131072;
constexpr int CH_OFF_MEM = CH_OFF_KV + CH_NKV * CH_KV_BYTES;
constexpr int CH_OFF_RS = CH_OFF_MEM + 8192;
constexpr int CH_OFF_STG = CH_OFF_RS + 8192;
constexpr int CH_OFF_Q = CH_OFF_STG + 512;
constexpr int CH_OFF_O = CH_OFF_Q + 1152;
constexpr int CH_OFF_RED1 = CH_OFF_O + 2176;
constexpr int CH_OFF_SC = CH_OFF_RED1 + 6144;
constexpr int CH_OFF_RED2 = CH_OFF_SC + 1280;
constexpr int CH_OFF_ZERO = CH_OFF_RED2 + 2048;
constexpr int CH_OFF_BAR = CH_OFF_ZERO + 128;
constexpr int CH_OFF_TS = CH_OFF_BAR + 256;
constexpr int CH_SMEM = CH_OFF_TS + 1024;

__device__ __forceinline__ uint32_t mapa_u32(uint32_t addr, uint32_t rank) {
    uint32_t r; asm volatile("mapa.shared::cluster.u32 %0, %1, %2;" : "=r"(r) : "r"(addr), "r"(rank)); return r;
}
__device__ __forceinline__ void st_async_v4(uint32_t addr, uint32_t a, uint32_t b, uint32_t c, uint32_t d, uint32_t mbar) {
    asm volatile("st.async.shared::cluster.mbarrier::complete_tx::bytes.v4.b32 [%0], {%1,%2,%3,%4}, [%5];"
                 :: "r"(addr), "r"(a), "r"(b), "r"(c), "r"(d), "r"(mbar) : "memory");
}
__device__ __forceinline__ void st_async_v2(uint32_t addr, uint32_t a, uint32_t b, uint32_t mbar) {
    asm volatile("st.async.shared::cluster.mbarrier::complete_tx::bytes.v2.b32 [%0], {%1,%2}, [%3];"
                 :: "r"(addr), "r"(a), "r"(b), "r"(mbar) : "memory");
}
__device__ __forceinline__ bool mbar_try_wait_cl(uint32_t bar, uint32_t parity) {
    uint32_t ok;
    asm volatile("{\n.reg .pred p;\nmbarrier.try_wait.parity.acquire.cluster.shared::cta.b64 p, [%1], %2;\nselp.u32 %0, 1, 0, p;\n}"
                 : "=r"(ok) : "r"(bar), "r"(parity) : "memory");
    return ok != 0;
}
__device__ __forceinline__ void mbar_wait_cl(uint32_t bar, uint32_t parity) {
    uint32_t n = 0;
    while (!mbar_try_wait_cl(bar, parity)) { if (++n > (1u << 20)) break; }
}
__device__ __forceinline__ void cluster_sync_all() {
    asm volatile("barrier.cluster.arrive.aligned;\nbarrier.cluster.wait.aligned;" ::: "memory");
}
__device__ __forceinline__ uint4 ld_relaxed_v4(const void* p) {
    uint4 v;
    asm volatile("ld.relaxed.gpu.global.v4.u32 {%0,%1,%2,%3}, [%4];" : "=r"(v.x), "=r"(v.y), "=r"(v.z), "=r"(v.w) : "l"(p) : "memory");
    return v;
}
__device__ __forceinline__ void st_relaxed_v4(void* p, uint32_t a, uint32_t b, uint32_t c, uint32_t d) {
    asm volatile("st.relaxed.gpu.global.v4.u32 [%0], {%1,%2,%3,%4};" :: "l"(p), "r"(a), "r"(b), "r"(c), "r"(d) : "memory");
}
__device__ __forceinline__ unsigned int ld_acquire_u32(const unsigned int* p) {
    unsigned int v;
    asm volatile("ld.acquire.gpu.global.u32 %0, [%1];" : "=r"(v) : "l"(p) : "memory");
    return v;
}
__device__ __forceinline__ void lds128(uint32_t* r, uint32_t addr) {
    asm volatile("ld.shared.v4.u32 {%0,%1,%2,%3}, [%4];" : "=r"(r[0]), "=r"(r[1]), "=r"(r[2]), "=r"(r[3]) : "r"(addr) : "memory");
}
__device__ __forceinline__ float ex2_approx(float x) { float y; asm("ex2.approx.ftz.f32 %0, %1;" : "=f"(y) : "f"(x)); return y; }
__device__ __forceinline__ void mma_nv(float* c, const uint32_t* a, uint32_t b0, uint32_t b1) {
    asm("mma.sync.aligned.m16n8k16.row.col.f32.bf16.bf16.f32 {%0,%1,%2,%3}, {%4,%5,%6,%7}, {%8,%9}, {%0,%1,%2,%3};"
        : "+f"(c[0]), "+f"(c[1]), "+f"(c[2]), "+f"(c[3]) : "r"(a[0]), "r"(a[1]), "r"(a[2]), "r"(a[3]), "r"(b0), "r"(b1));
}

__device__ __forceinline__ void st_relaxed_v2(void* p, uint32_t a, uint32_t b) {
    asm volatile("st.relaxed.gpu.global.v2.u32 [%0], {%1,%2};" :: "l"(p), "r"(a), "r"(b) : "memory");
}

#define TSX(i)
__global__ void __launch_bounds__(384, 1) chain_kernel(const __grid_constant__ ChainParams p) {
    extern __shared__ __align__(1024) unsigned char smem[];
    const uint32_t sb = smem_u32(smem);
    int tid; asm volatile("mov.u32 %0, %%tid.x;" : "=r"(tid));
    int bid; asm volatile("mov.u32 %0, %%ctaid.x;" : "=r"(bid));
    const int lane = tid & 31;
    const int warp = __shfl_sync(0xffffffff, tid >> 5, 0);
    const int wgi = __shfl_sync(0xffffffff, tid >> 7, 0);
    const int rank = bid & 15, cl = bid >> 4;
    const int head = bid >> 1, half = bid & 1;
    const uint32_t barSc = sb + CH_OFF_BAR, barV = barSc + 8, barLd = barSc + 16, barKV = barSc + 24, barMem = barKV + 8 * CH_NKV, barRS = barMem + 8;

    if (tid == 0) {
        mbar_init(barSc, 1); mbar_init(barV, 1); mbar_init(barLd, 1); mbar_init(barMem, 1); mbar_init(barRS, 1);
        for (int i = 0; i < CH_NKV; i++) mbar_init(barKV + 8 * i, 1);
        fence_mbar_init();
        mbar_expect_tx(barSc, 1280);
        mbar_expect_tx(barV, 1024);
        mbar_expect_tx(barMem, 8192);
        mbar_expect_tx(barRS, 8192);
    }
    if (tid < 32) *reinterpret_cast<uint32_t*>(smem + CH_OFF_ZERO + tid * 4) = 0u;
    __syncthreads();
    cluster_sync_all();
    const uint32_t peer = rank ^ 1;
    const int t4 = lane & 3, g8 = lane >> 2;
    const int lr = lane & 7, lm = lane >> 3;

    if (wgi < 2) {
        reg_alloc<208>();
        const int g = warp >> 1, kh = warp & 1;
        uint32_t wqk[2][16][4];
        {
            const int c64 = head * 2 + half;
            const int krow = lr + ((lane >> 4) & 1) * 8;
            const int chunk = g * 2 + (lm & 1);
            if (tid == 0) {
                mbar_expect_tx(barLd, 131072);
                tma_load_3d(sb + CH_OFF_WO, &p.tmW[0], 0, 0, c64, barLd);
                tma_load_3d(sb + CH_OFF_WO + 32768, &p.tmW[0], 0, 256, c64, barLd);
                tma_load_3d(sb + CH_OFF_WV, &p.tmW[1], 0, 0, c64, barLd);
                tma_load_3d(sb + CH_OFF_WV + 32768, &p.tmW[1], 0, 256, c64, barLd);
            }
            mbar_wait(barLd, 0);
#pragma unroll
            for (int m = 0; m < 2; m++)
#pragma unroll
                for (int ks = 0; ks < 16; ks++) {
                    int r = kh * 256 + ks * 16 + krow;
                    uint32_t addr = sb + (m == 0 ? CH_OFF_WO : CH_OFF_WV) + r * 128 + ((chunk ^ (r & 7)) << 4);
                    ldmatrix_x4_t(wqk[m][ks][0], wqk[m][ks][1], wqk[m][ks][2], wqk[m][ks][3], addr);
                }
            named_bar_sync(7, 256);
            if (tid == 0) {
                mbar_expect_tx(barLd, 131072);
                tma_load_3d(sb + CH_OFF_WV, &p.tmW[2], 0, 0, c64, barLd);
                tma_load_3d(sb + CH_OFF_WV + 32768, &p.tmW[2], 0, 256, c64, barLd);
                for (int i = 0; i < 4; i++) tma_load_3d(sb + CH_OFF_WO + i * 16384, &p.tmWo, 0, head * 128, half * 4 + i, barLd);
            }
            mbar_wait(barLd, 1);
            uint32_t f[16][4];
#pragma unroll
            for (int ks = 0; ks < 16; ks++) {
                int r = kh * 256 + ks * 16 + krow;
                ldmatrix_x4_t(f[ks][0], f[ks][1], f[ks][2], f[ks][3], sb + CH_OFF_WV + r * 128 + ((chunk ^ (r & 7)) << 4));
            }
            named_bar_sync(7, 256);
#pragma unroll
            for (int ks = 0; ks < 16; ks++)
                asm volatile("st.shared.v4.u32 [%0], {%1,%2,%3,%4};" :: "r"(sb + CH_OFF_WV + ((warp * 16 + ks) * 32 + lane) * 16), "r"(f[ks][0]), "r"(f[ks][1]), "r"(f[ks][2]), "r"(f[ks][3]) : "memory");
#pragma unroll
            for (int ks = 0; ks < 8; ks++)
#pragma unroll
                for (int mt = 0; mt < 2; mt++) {
                    int r = ks * 16 + krow;
                    int colchunk = warp * 4 + mt * 2 + (lm & 1);
                    ldmatrix_x4_t(f[ks * 2 + mt][0], f[ks * 2 + mt][1], f[ks * 2 + mt][2], f[ks * 2 + mt][3],
                                  sb + CH_OFF_WO + (colchunk >> 3) * 16384 + r * 128 + (((colchunk & 7) ^ (r & 7)) << 4));
                }
            named_bar_sync(7, 256);
#pragma unroll
            for (int i = 0; i < 16; i++)
                asm volatile("st.shared.v4.u32 [%0], {%1,%2,%3,%4};" :: "r"(sb + CH_OFF_WO + ((warp * 16 + i) * 32 + lane) * 16), "r"(f[i][0]), "r"(f[i][1]), "r"(f[i][2]), "r"(f[i][3]) : "memory");
            named_bar_sync(7, 256);
        }
        const uint32_t wvbase = sb + CH_OFF_WV + (warp * 16 * 32 + lane) * 16;
        const uint32_t wobase = sb + CH_OFF_WO + (warp * 16 * 32 + lane) * 16;
        const uint32_t bAddr = sb + CH_OFF_MEM + kh * 4096 + lr * 64 + ((lm ^ ((lr >> 1) & 3)) << 4);
        const uint32_t redMine = sb + CH_OFF_RED1 + warp * 512 + lane * 16, redOther = sb + CH_OFF_RED1 + (warp ^ 1) * 512 + lane * 16;
        const uint32_t redMineV = sb + CH_OFF_RED1 + 4096 + warp * 256 + lane * 8, redOtherV = sb + CH_OFF_RED1 + 4096 + (warp ^ 1) * 256 + lane * 8;
        const uint32_t qDst = sb + CH_OFF_Q + lr * CH_Q_STRIDE + (g * 16 + (lm & 1) * 8) * 2;
        const uint32_t kvOff = lr * 128 + (((g * 2 + (lm & 1)) ^ lr) << 4);
        const uint32_t peerBase = mapa_u32(sb, peer) - sb;
        const uint32_t oAddr = sb + CH_OFF_O + lr * CH_O_STRIDE + lm * 16;
        const uint32_t rsDst = mapa_u32(sb + CH_OFF_RS + (rank >> 1) * 1024 + lane * 16, warp * 2 + half);
        const uint32_t rsBar = mapa_u32(barRS, warp * 2 + half);
        float* llW = p.part + ((size_t)(cl * 16 + rank) * 64 + tid) * 4;
        for (int s = 0; s < NSTEPS; s++) {
            const uint32_t sKV = sb + CH_OFF_KV + (s & (CH_NKV - 1)) * CH_KV_BYTES;
            uint32_t wo[16][4], wv[2][2][4];
#pragma unroll
            for (int i = 0; i < 8; i++) lds128(wo[i], wobase + i * 512);
            lds128(wv[0][0], wvbase); lds128(wv[0][1], wvbase + 512);
            TSX(0);
            if (s == 0) {
                for (int i = tid; i < 512; i += 256) {
                    int tok = i & 7, c = i >> 3;
                    uint4 v = *reinterpret_cast<const uint4*>(p.mem0 + tok * 512 + c * 8);
                    *reinterpret_cast<uint4*>(smem + CH_OFF_MEM + (c >> 2) * 512 + tok * 64 + (((c & 3) ^ ((tok >> 1) & 3)) << 4)) = v;
                }
                named_bar_sync(7, 256);
            } else {
                mbar_wait(barMem, (s - 1) & 1);
                if (tid == 0) mbar_expect_tx(barMem, 8192);
            }
            TSX(1);
            {
                float aq[4], ak[4], av[4];
#pragma unroll
                for (int i = 0; i < 4; i++) { aq[i] = ak[i] = av[i] = 0.f; }
                uint32_t b[2][4];
                ldmatrix_x4(b[0][0], b[0][1], b[0][2], b[0][3], bAddr);
#pragma unroll
                for (int kk = 0; kk < 8; kk++) {
                    if (kk + 1 < 8) {
                        ldmatrix_x4(b[(kk + 1) & 1][0], b[(kk + 1) & 1][1], b[(kk + 1) & 1][2], b[(kk + 1) & 1][3], bAddr + (kk + 1) * 512);
                        lds128(wv[(kk + 1) & 1][0], wvbase + (2 * kk + 2) * 512);
                        lds128(wv[(kk + 1) & 1][1], wvbase + (2 * kk + 3) * 512);
                    }
                    mma_nv(aq, wqk[0][2 * kk], b[kk & 1][0], b[kk & 1][1]);
                    mma_nv(ak, wqk[1][2 * kk], b[kk & 1][0], b[kk & 1][1]);
                    mma_nv(av, wv[kk & 1][0], b[kk & 1][0], b[kk & 1][1]);
                    mma_nv(aq, wqk[0][2 * kk + 1], b[kk & 1][2], b[kk & 1][3]);
                    mma_nv(ak, wqk[1][2 * kk + 1], b[kk & 1][2], b[kk & 1][3]);
                    mma_nv(av, wv[kk & 1][1], b[kk & 1][2], b[kk & 1][3]);
                }
                TSX(2);
                float gv[6], kp[6];
#pragma unroll
                for (int i = 0; i < 4; i++) {
                    gv[i] = kh == 0 ? ak[i] : aq[i];
                    kp[i] = kh == 0 ? aq[i] : ak[i];
                }
                gv[4] = kh == 0 ? av[2] : av[0]; gv[5] = kh == 0 ? av[3] : av[1];
                kp[4] = kh == 0 ? av[0] : av[2]; kp[5] = kh == 0 ? av[1] : av[3];
                asm volatile("st.shared.v4.f32 [%0], {%1,%2,%3,%4};" :: "r"(redMine), "f"(gv[0]), "f"(gv[1]), "f"(gv[2]), "f"(gv[3]) : "memory");
                asm volatile("st.shared.v2.f32 [%0], {%1,%2};" :: "r"(redMineV), "f"(gv[4]), "f"(gv[5]) : "memory");
                named_bar_sync(1 + g, 64);
                float o0, o1, o2, o3, o4, o5;
                asm volatile("ld.shared.v4.f32 {%0,%1,%2,%3}, [%4];" : "=f"(o0), "=f"(o1), "=f"(o2), "=f"(o3) : "r"(redOther) : "memory");
                asm volatile("ld.shared.v2.f32 {%0,%1}, [%2];" : "=f"(o4), "=f"(o5) : "r"(redOtherV) : "memory");
                uint32_t r0 = pack_bf16(kp[0] + o0, kp[1] + o1);
                uint32_t r1 = pack_bf16(kp[2] + o2, kp[3] + o3);
                uint32_t r2 = pack_bf16(kp[4] + o4, kp[5] + o5);
                asm volatile("stmatrix.sync.aligned.m8n8.x2.trans.shared.b16 [%0], {%1,%2};" :: "r"(kh == 0 ? qDst : sKV + kvOff), "r"(r0), "r"(r1) : "memory");
                const uint32_t vAddr = sKV + 5120 + half * 5120 + lr * 128 + (((g * 2 + kh) ^ lr) << 4);
                asm volatile("stmatrix.sync.aligned.m8n8.x1.trans.shared.b16 [%0], {%1};" :: "r"(vAddr), "r"(r2) : "memory");
                named_bar_arrive(5, 384);
                TSX(3);
                __syncwarp();
                if (lane < 8) {
                    uint32_t f[4];
                    lds128(f, vAddr);
                    st_async_v4(vAddr + peerBase, f[0], f[1], f[2], f[3], barV + peerBase);
                }
            }
            if (s == NSTEPS - 1) break;
            named_bar_sync(10, 384);
#pragma unroll
            for (int i = 8; i < 16; i++) {
                lds128(wo[i], wobase + i * 512);
            }
            TSX(4);
            named_bar_sync(8, 384);
            TSX(5);
            const uint32_t tag = ((s >> 1) + 1) & 1;
            const uint32_t slotOff = (s & 1) * (64 * 256);
            {
                float a2[2][2][4];
#pragma unroll
                for (int i = 0; i < 4; i++) { a2[0][0][i] = a2[0][1][i] = a2[1][0][i] = a2[1][1][i] = 0.f; }
                uint32_t b[4][4];
#pragma unroll
                for (int kk = 0; kk < 4; kk++) ldmatrix_x4(b[kk][0], b[kk][1], b[kk][2], b[kk][3], oAddr + kk * 64);
#pragma unroll
                for (int kk = 0; kk < 4; kk++) {
                    mma_nv(a2[0][0], wo[kk * 4 + 0], b[kk][0], b[kk][1]);
                    mma_nv(a2[1][0], wo[kk * 4 + 1], b[kk][0], b[kk][1]);
                    mma_nv(a2[0][1], wo[kk * 4 + 2], b[kk][2], b[kk][3]);
                    mma_nv(a2[1][1], wo[kk * 4 + 3], b[kk][2], b[kk][3]);
                }
#pragma unroll
                for (int mt = 0; mt < 2; mt++) {
                    float c0 = a2[mt][0][0] + a2[mt][1][0], c1 = a2[mt][0][1] + a2[mt][1][1];
                    float c2 = a2[mt][0][2] + a2[mt][1][2], c3 = a2[mt][0][3] + a2[mt][1][3];
                    st_async_v4(rsDst + mt * 512, __float_as_uint(c0), __float_as_uint(c1), __float_as_uint(c2), __float_as_uint(c3), rsBar);
                }
            }
            TSX(6);
            if (warp < 2) {
                mbar_wait(barRS, s & 1);
                TSX(7);
                float4 u[8];
#pragma unroll
                for (int h = 0; h < 8; h++)
                    asm volatile("ld.shared.v4.f32 {%0,%1,%2,%3}, [%4];" : "=f"(u[h].x), "=f"(u[h].y), "=f"(u[h].z), "=f"(u[h].w) : "r"(sb + CH_OFF_RS + h * 1024 + tid * 16) : "memory");
                if (tid == 0) mbar_expect_tx(barRS, 8192);
                float f0 = ((u[0].x + u[1].x) + (u[2].x + u[3].x)) + ((u[4].x + u[5].x) + (u[6].x + u[7].x));
                float f1 = ((u[0].y + u[1].y) + (u[2].y + u[3].y)) + ((u[4].y + u[5].y) + (u[6].y + u[7].y));
                float f2 = ((u[0].z + u[1].z) + (u[2].z + u[3].z)) + ((u[4].z + u[5].z) + (u[6].z + u[7].z));
                float f3 = ((u[0].w + u[1].w) + (u[2].w + u[3].w)) + ((u[4].w + u[5].w) + (u[6].w + u[7].w));
                const uint32_t x0 = (__float_as_uint(f0) & ~1u) | tag;
                st_relaxed_v4(llW + slotOff, x0, __float_as_uint(f1), __float_as_uint(f2), __float_as_uint(f3));
                const float* r1 = p.part + slotOff + ((size_t)((cl ^ 1) * 16 + rank) * 64 + tid) * 4;
                const float* r2 = p.part + slotOff + ((size_t)((cl ^ 2) * 16 + rank) * 64 + tid) * 4;
                const float* r3 = p.part + slotOff + ((size_t)((cl ^ 3) * 16 + rank) * 64 + tid) * 4;
                uint4 v1, v2, v3;
                uint32_t n = 0;
                do { v1 = ld_relaxed_v4(r1); v2 = ld_relaxed_v4(r2); v3 = ld_relaxed_v4(r3); }
                while (POLL_R && (((v1.x ^ tag) | (v2.x ^ tag) | (v3.x ^ tag)) & 1u) && ++n < (1u << 22));
                TSX(8);
                f0 = (__uint_as_float(x0) + __uint_as_float(v1.x)) + (__uint_as_float(v2.x) + __uint_as_float(v3.x));
                f1 = (f1 + __uint_as_float(v1.y)) + (__uint_as_float(v2.y) + __uint_as_float(v3.y));
                f2 = (f2 + __uint_as_float(v1.z)) + (__uint_as_float(v2.z) + __uint_as_float(v3.z));
                f3 = (f3 + __uint_as_float(v1.w)) + (__uint_as_float(v2.w) + __uint_as_float(v3.w));
                const int ch = warp * 2 + (lm & 1);
                asm volatile("stmatrix.sync.aligned.m8n8.x2.trans.shared.b16 [%0], {%1,%2};"
                             :: "r"(sb + CH_OFF_STG + lr * 64 + ((ch ^ ((lr >> 1) & 3)) << 4)), "r"(pack_bf16(f0, f1)), "r"(pack_bf16(f2, f3)) : "memory");
                named_bar_sync(9, 64);
                uint32_t f[4];
                lds128(f, sb + CH_OFF_STG + lane * 16);
                const uint32_t dst0 = sb + CH_OFF_MEM + (half * 8 + (rank >> 1)) * 512 + lane * 16;
#pragma unroll
                for (int d = 0; d < 8; d++) {
                    const uint32_t dr = warp * 8 + d;
                    st_async_v4(mapa_u32(dst0, dr), f[0], f[1], f[2], f[3], mapa_u32(barMem, dr));
                }
                TSX(9);
            }
        }
    } else {
        reg_dealloc<88>();
        const int aw = warp - 8;
        const uint32_t peerBase = mapa_u32(sb, peer) - sb;
        const float sm_scale = 0.08838834764831845f * 1.4426950408889634f;
        const int kc64 = 64 + head * 2 + half, vc64 = 128 + head * 2;
        auto issue_kv = [&](int s) {
            if ((s & 3) == 0) {
                uint32_t n = 0;
                while (ld_acquire_u32(p.flags + (s >> 2)) < p.flag_target) { if (++n > (1u << 22)) break; }
                fence_proxy_async_all();
            }
            int st = s & (CH_NKV - 1);
            uint32_t base = sb + CH_OFF_KV + st * CH_KV_BYTES;
            mbar_expect_tx(barKV + 8 * st, 12288);
            tma_load_3d(base + 1024, &p.tmKV, 0, s * 32, kc64, barKV + 8 * st);
            tma_load_3d(base + 5120 + 1024, &p.tmKV, 0, s * 32, vc64, barKV + 8 * st);
            tma_load_3d(base + 10240 + 1024, &p.tmKV, 0, s * 32, vc64 + 1, barKV + 8 * st);
        };
        if (aw == 3 && lane == 0) { for (int s = 0; s < CH_NKV - 1; s++) issue_kv(s); }
        const uint32_t kOff0 = lr * 128 + ((lm ^ lr) << 4), kOff1 = lr * 128 + (((4 + lm) ^ lr) << 4);
        const uint32_t qAddr = (lm & 1) ? (sb + CH_OFF_ZERO) : (sb + CH_OFF_Q + lr * CH_Q_STRIDE + (lm >> 1) * 16);
        const uint32_t qStep = (lm & 1) ? 0u : 32u;
        const uint32_t vRow = ((lm >> 1) * 8 + lr) * 128;
        const uint32_t vOff0 = 5120 + (aw >> 1) * 5120 + vRow + ((((aw & 1) * 4 + (lm & 1)) ^ lr) << 4);
        const uint32_t vOff1 = 5120 + (aw >> 1) * 5120 + vRow + ((((aw & 1) * 4 + 2 + (lm & 1)) ^ lr) << 4);
        const uint32_t padAdj = (lm >> 1) ? 2048u : 0u;
        const uint32_t scAddr = sb + CH_OFF_SC + lane * 8;
        const uint32_t oDst = sb + CH_OFF_O + lr * CH_O_STRIDE + (aw * 32 + lm * 8) * 2;
        const int si = tid - 256, sw = si >> 6, stok = (si >> 3) & 7, scn = si & 7;
        const uint32_t kvmOff = (sw == 0 ? 0u : 5120u + half * 5120u) + stok * 128 + ((scn ^ stok) << 4);
        bf16* kvmDst = p.kvmem + (size_t)stok * 8192 + sw * 4096 + head * 128 + half * 64 + scn * 8;
        const bool leader = (tid == 256);
        for (int s = 0; s < NSTEPS; s++) {
            const uint32_t par = s & 1;
            const int st = s & (CH_NKV - 1);
            const uint32_t sKV = sb + CH_OFF_KV + st * CH_KV_BYTES;
            mbar_wait(barKV + 8 * st, (s / CH_NKV) & 1);
            uint32_t kb[2][4][4], va[3][2][4];
#pragma unroll
            for (int n = 0; n < 4; n++) {
                ldmatrix_x4(kb[0][n][0], kb[0][n][1], kb[0][n][2], kb[0][n][3], sKV + (n + 1) * 1024 + kOff0);
                ldmatrix_x4(kb[1][n][0], kb[1][n][1], kb[1][n][2], kb[1][n][3], sKV + (n + 1) * 1024 + kOff1);
            }
            TSX(0);
            named_bar_sync(5, 384);
            TSX(1);
            float sc[5][4];
#pragma unroll
            for (int n = 0; n < 5; n++) { sc[n][0] = sc[n][1] = sc[n][2] = sc[n][3] = 0.f; }
            {
                uint32_t a[4][4], km[2][4];
#pragma unroll
                for (int k = 0; k < 4; k++) ldmatrix_x4(a[k][0], a[k][1], a[k][2], a[k][3], qAddr + k * qStep);
                ldmatrix_x4(km[0][0], km[0][1], km[0][2], km[0][3], sKV + kOff0);
                ldmatrix_x4(km[1][0], km[1][1], km[1][2], km[1][3], sKV + kOff1);
#pragma unroll
                for (int kp = 0; kp < 2; kp++) {
#pragma unroll
                    for (int n = 0; n < 4; n++) mma_nv(sc[n + 1], a[kp * 2], kb[kp][n][0], kb[kp][n][1]);
#pragma unroll
                    for (int n = 0; n < 4; n++) mma_nv(sc[n + 1], a[kp * 2 + 1], kb[kp][n][2], kb[kp][n][3]);
                }
                mma_nv(sc[0], a[0], km[0][0], km[0][1]);
                mma_nv(sc[0], a[1], km[0][2], km[0][3]);
                mma_nv(sc[0], a[2], km[1][0], km[1][1]);
                mma_nv(sc[0], a[3], km[1][2], km[1][3]);
            }
            TSX(2);
            if (aw == 0) {
#pragma unroll
                for (int n = 0; n < 5; n++) st_async_v2(scAddr + peerBase + n * 256, __float_as_uint(sc[n][0]), __float_as_uint(sc[n][1]), barSc + peerBase);
            }
#pragma unroll
            for (int ks = 1; ks < 3; ks++) {
                const uint32_t adj = ks == 2 ? padAdj : 0u;
                ldmatrix_x4_t(va[ks][0][0], va[ks][0][1], va[ks][0][2], va[ks][0][3], sKV + ks * 2048 + vOff0 - adj);
                ldmatrix_x4_t(va[ks][1][0], va[ks][1][1], va[ks][1][2], va[ks][1][3], sKV + ks * 2048 + vOff1 - adj);
            }
            uint4 kvm;
            if (s < NSTEPS - 1) named_bar_arrive(10, 384);
            if (sw == 0) asm volatile("ld.shared.v4.u32 {%0,%1,%2,%3}, [%4];" : "=r"(kvm.x), "=r"(kvm.y), "=r"(kvm.z), "=r"(kvm.w) : "r"(sKV + kvmOff) : "memory");
            TSX(3);
            mbar_wait(barSc, par);
            TSX(4);
            float pp[5][2];
#pragma unroll
            for (int n = 0; n < 5; n++)
                asm volatile("ld.shared.v2.f32 {%0,%1}, [%2];" : "=f"(pp[n][0]), "=f"(pp[n][1]) : "r"(scAddr + n * 256) : "memory");
            if (leader) mbar_expect_tx(barSc, 1280);
#pragma unroll
            for (int n = 0; n < 5; n++) { sc[n][0] += pp[n][0]; sc[n][1] += pp[n][1]; }
            float mx = fmaxf(fmaxf(fmaxf(sc[0][0], sc[0][1]), fmaxf(sc[1][0], sc[1][1])), fmaxf(fmaxf(sc[2][0], sc[2][1]), fmaxf(sc[3][0], sc[3][1])));
            mx = fmaxf(mx, fmaxf(sc[4][0], sc[4][1]));
            mx = fmaxf(mx, __shfl_xor_sync(0xffffffff, mx, 1));
            mx = fmaxf(mx, __shfl_xor_sync(0xffffffff, mx, 2));
            const float mb = mx * sm_scale;
            uint32_t pb[5];
            float e[5][2];
#pragma unroll
            for (int n = 0; n < 5; n++) {
                e[n][0] = ex2_approx(fmaf(sc[n][0], sm_scale, -mb));
                e[n][1] = ex2_approx(fmaf(sc[n][1], sm_scale, -mb));
                pb[n] = pack_bf16(e[n][0], e[n][1]);
            }
            TSX(5);
            float oc[2][4];
#pragma unroll
            for (int i = 0; i < 4; i++) { oc[0][i] = oc[1][i] = 0.f; }
            mma_nv(oc[0], va[1][0], pb[2], pb[3]);
            mma_nv(oc[1], va[1][1], pb[2], pb[3]);
            mma_nv(oc[0], va[2][0], pb[4], 0u);
            mma_nv(oc[1], va[2][1], pb[4], 0u);
            float sum = ((e[0][0] + e[0][1]) + (e[1][0] + e[1][1])) + ((e[2][0] + e[2][1]) + (e[3][0] + e[3][1])) + (e[4][0] + e[4][1]);
            sum += __shfl_xor_sync(0xffffffff, sum, 1);
            sum += __shfl_xor_sync(0xffffffff, sum, 2);
            const float inv = __fdividef(1.0f, sum);
            const float i0 = __shfl_sync(0xffffffff, inv, t4 * 8), i1 = __shfl_sync(0xffffffff, inv, t4 * 8 + 4);
            TSX(6);
            mbar_wait(barV, par);
            TSX(7);
            ldmatrix_x4_t(va[0][0][0], va[0][0][1], va[0][0][2], va[0][0][3], sKV + vOff0);
            ldmatrix_x4_t(va[0][1][0], va[0][1][1], va[0][1][2], va[0][1][3], sKV + vOff1);
            if (leader) mbar_expect_tx(barV, 1024);
            if (sw == 1) asm volatile("ld.shared.v4.u32 {%0,%1,%2,%3}, [%4];" : "=r"(kvm.x), "=r"(kvm.y), "=r"(kvm.z), "=r"(kvm.w) : "r"(sKV + kvmOff) : "memory");
            mma_nv(oc[0], va[0][0], pb[0], pb[1]);
            mma_nv(oc[1], va[0][1], pb[0], pb[1]);
            stmatrix_x4_t(oDst, pack_bf16(oc[0][0] * i0, oc[0][1] * i1), pack_bf16(oc[0][2] * i0, oc[0][3] * i1),
                          pack_bf16(oc[1][0] * i0, oc[1][1] * i1), pack_bf16(oc[1][2] * i0, oc[1][3] * i1));
            if (s < NSTEPS - 1) named_bar_arrive(8, 384);
            TSX(8);
            *reinterpret_cast<uint4*>(kvmDst + (size_t)s * 65536) = kvm;
            if (p.seg_flags) { __syncwarp(); if (lane == 0) { __threadfence(); atomicAdd(p.seg_flags + s, 1u); } }
            if (aw == 3 && lane == 0 && s + CH_NKV - 1 < NSTEPS) issue_kv(s + CH_NKV - 1);
        }
    }
    __syncthreads();
    cluster_sync_all();
}

struct AttnAParams {
    CUtensorMap tmKV;
    const bf16* qkv;
    bf16* o;
};
constexpr int AA_KT = 256;
constexpr int AA_NST = 3;
constexpr int AA_SMEM = AA_NST * 2 * AA_KT * 32 + 64;

__device__ __forceinline__ float ex2a(float x) { float y; asm("ex2.approx.ftz.f32 %0, %1;" : "=f"(y) : "f"(x)); return y; }
__device__ __forceinline__ void mma_f(float* c, const uint32_t* a, uint32_t b0, uint32_t b1) {
    asm("mma.sync.aligned.m16n8k16.row.col.f32.bf16.bf16.f32 {%0,%1,%2,%3}, {%4,%5,%6,%7}, {%8,%9}, {%0,%1,%2,%3};"
        : "+f"(c[0]), "+f"(c[1]), "+f"(c[2]), "+f"(c[3]) : "r"(a[0]), "r"(a[1]), "r"(a[2]), "r"(a[3]), "r"(b0), "r"(b1));
}

__global__ void __launch_bounds__(256, 2) attn_a_kernel(const __grid_constant__ AttnAParams p) {
    extern __shared__ __align__(1024) unsigned char smem[];
    const uint32_t sb = smem_u32(smem);
    const uint32_t bars = sb + AA_NST * 2 * AA_KT * 32;
    const int tid = threadIdx.x, lane = tid & 31, warp = tid >> 5;
    const int head = blockIdx.x >> 3, qt = blockIdx.x & 7;
    const int t4 = lane & 3, g8 = lane >> 2;
    constexpr int NT = 2048 / AA_KT;

    if (tid == 0) {
        for (int i = 0; i < AA_NST; i++) { mbar_init(bars + 8 * i, 1); mbar_init(bars + 8 * (AA_NST + i), 8); }
        fence_mbar_init();
    }
    __syncthreads();
    auto issue = [&](int t) {
        int st = t % AA_NST;
        uint32_t dst = sb + st * (2 * AA_KT * 32);
        mbar_expect_tx(bars + 8 * st, 2 * AA_KT * 32);
        tma_load_2d(dst, &p.tmKV, 512 + head * 16, t * AA_KT, bars + 8 * st);
        tma_load_2d(dst + AA_KT * 32, &p.tmKV, 1024 + head * 16, t * AA_KT, bars + 8 * st);
    };
    if (tid == 0) { for (int t = 0; t < AA_NST; t++) issue(t); }

    uint32_t qa[2][4];
    const int row0 = qt * 256 + warp * 32;
#pragma unroll
    for (int m = 0; m < 2; m++) {
        const bf16* q = p.qkv + (size_t)(row0 + m * 16 + g8) * 1536 + head * 16 + t4 * 2;
        qa[m][0] = *reinterpret_cast<const uint32_t*>(q);
        qa[m][1] = *reinterpret_cast<const uint32_t*>(q + 8 * 1536);
        qa[m][2] = *reinterpret_cast<const uint32_t*>(q + 8);
        qa[m][3] = *reinterpret_cast<const uint32_t*>(q + 8 * 1536 + 8);
    }
    const float sc = 0.25f * 1.4426950408889634f;
    float mrow[2][2], oacc[2][2][4], lacc[2][4];
#pragma unroll
    for (int m = 0; m < 2; m++) {
        mrow[m][0] = mrow[m][1] = -3.0e38f;
#pragma unroll
        for (int i = 0; i < 4; i++) { oacc[m][0][i] = oacc[m][1][i] = 0.f; lacc[m][i] = 0.f; }
    }
    const uint32_t ones = 0x3F803F80u;
    const int lr = lane & 7, lm = lane >> 3;
    const int krow = (lm >> 1) * 8 + lr, kch = lm & 1;
    const uint32_t koff = krow * 32 + ((kch ^ ((krow >> 2) & 1)) << 4);
    const int vrow = (lm & 1) * 8 + lr, vch = lm >> 1;
    const uint32_t voff = vrow * 32 + ((vch ^ ((vrow >> 2) & 1)) << 4);

    for (int t = 0; t < NT; t++) {
        const int st = t % AA_NST;
        mbar_wait(bars + 8 * st, (t / AA_NST) & 1);
        const uint32_t sK = sb + st * (2 * AA_KT * 32), sV = sK + AA_KT * 32;
#pragma unroll 1
        for (int kb = 0; kb < AA_KT / 64; kb++) {
            float s[2][8][4];
#pragma unroll
            for (int np = 0; np < 4; np++) {
                uint32_t b0, b1, b2, b3;
                ldmatrix_x4(b0, b1, b2, b3, sK + (kb * 64 + np * 16) * 32 + koff);
#pragma unroll
                for (int m = 0; m < 2; m++) {
#pragma unroll
                    for (int i = 0; i < 4; i++) { s[m][np * 2][i] = 0.f; s[m][np * 2 + 1][i] = 0.f; }
                    mma_f(s[m][np * 2], qa[m], b0, b1);
                    mma_f(s[m][np * 2 + 1], qa[m], b2, b3);
                }
            }
            uint32_t pa[2][4][4];
#pragma unroll
            for (int m = 0; m < 2; m++) {
                float mx0 = s[m][0][0], mx1 = s[m][0][2];
#pragma unroll
                for (int n = 0; n < 8; n++) {
                    mx0 = fmaxf(mx0, fmaxf(s[m][n][0], s[m][n][1]));
                    mx1 = fmaxf(mx1, fmaxf(s[m][n][2], s[m][n][3]));
                }
                mx0 = fmaxf(mx0, __shfl_xor_sync(0xffffffff, mx0, 1)); mx0 = fmaxf(mx0, __shfl_xor_sync(0xffffffff, mx0, 2));
                mx1 = fmaxf(mx1, __shfl_xor_sync(0xffffffff, mx1, 1)); mx1 = fmaxf(mx1, __shfl_xor_sync(0xffffffff, mx1, 2));
                const float mn0 = fmaxf(mrow[m][0], mx0), mn1 = fmaxf(mrow[m][1], mx1);
                const float a0 = ex2a((mrow[m][0] - mn0) * sc), a1 = ex2a((mrow[m][1] - mn1) * sc);
                mrow[m][0] = mn0; mrow[m][1] = mn1;
                const float mb0 = mn0 * sc, mb1 = mn1 * sc;
#pragma unroll
                for (int d = 0; d < 2; d++) { oacc[m][d][0] *= a0; oacc[m][d][1] *= a0; oacc[m][d][2] *= a1; oacc[m][d][3] *= a1; }
                lacc[m][0] *= a0; lacc[m][2] *= a1;
#pragma unroll
                for (int n = 0; n < 8; n++) {
                    float p0 = ex2a(fmaf(s[m][n][0], sc, -mb0)), p1 = ex2a(fmaf(s[m][n][1], sc, -mb0));
                    float p2 = ex2a(fmaf(s[m][n][2], sc, -mb1)), p3 = ex2a(fmaf(s[m][n][3], sc, -mb1));
                    pa[m][n >> 1][(n & 1) * 2 + 0] = pack_bf16(p0, p1);
                    pa[m][n >> 1][(n & 1) * 2 + 1] = pack_bf16(p2, p3);
                }
            }
#pragma unroll
            for (int ks = 0; ks < 4; ks++) {
                uint32_t b0, b1, b2, b3;
                ldmatrix_x4_t(b0, b1, b2, b3, sV + (kb * 64 + ks * 16) * 32 + voff);
#pragma unroll
                for (int m = 0; m < 2; m++) {
                    mma_f(oacc[m][0], pa[m][ks], b0, b1);
                    mma_f(oacc[m][1], pa[m][ks], b2, b3);
                    mma_f(lacc[m], pa[m][ks], ones, ones);
                }
            }
        }
        __syncwarp();
        if (lane == 0) mbar_arrive(bars + 8 * (AA_NST + st));
        if (tid == 0 && t + AA_NST < NT) {
            mbar_wait(bars + 8 * (AA_NST + st), (t / AA_NST) & 1);
            issue(t + AA_NST);
        }
    }
#pragma unroll
    for (int m = 0; m < 2; m++) {
        const float i0 = 1.0f / lacc[m][0], i1 = 1.0f / lacc[m][2];
        bf16* o = p.o + (size_t)(row0 + m * 16 + g8) * 512 + head * 16 + t4 * 2;
#pragma unroll
        for (int d = 0; d < 2; d++) {
            *reinterpret_cast<uint32_t*>(o + d * 8) = pack_bf16(oacc[m][d][0] * i0, oacc[m][d][1] * i0);
            *reinterpret_cast<uint32_t*>(o + 8 * 512 + d * 8) = pack_bf16(oacc[m][d][2] * i1, oacc[m][d][3] * i1);
        }
    }
}

struct AttnBParams {
    CUtensorMap tmQKV;
    CUtensorMap tmKVM;
    CUtensorMap tmO;
    const unsigned int* seg_flags;
    unsigned int seg_target;
    unsigned int* tile_flags;
};
constexpr int AB_WARP_BYTES = 28672;
constexpr int AB_SMEM = 4 * AB_WARP_BYTES + 64;

__global__ void __launch_bounds__(128, 2) attn_b_kernel(const __grid_constant__ AttnBParams p) {
    extern __shared__ __align__(1024) unsigned char smem[];
    const int tid = threadIdx.x, lane = tid & 31, warp = tid >> 5;
    const uint32_t sb = smem_u32(smem) + warp * AB_WARP_BYTES;
    const uint32_t bar = smem_u32(smem) + 4 * AB_WARP_BYTES + warp * 8;
    asm volatile("griddepcontrol.launch_dependents;" ::: "memory");
    const int seg = blockIdx.x >> 3, head = (blockIdx.x & 7) * 4 + warp;
    const int t4 = lane & 3, g8 = lane >> 2;
    const uint32_t sQ = sb, sK = sb + 8192, sV = sb + 16384, sKm = sb + 24576, sVm = sb + 26624;
    if (lane == 0) {
        mbar_init(bar, 1);
        fence_mbar_init();
        if (p.seg_flags) {
            uint32_t n = 0;
            while (ld_acquire_u32(p.seg_flags + seg) < p.seg_target) { if (++n > (1u << 24)) break; __nanosleep(200); }
            fence_proxy_async_all();
        }
        mbar_expect_tx(bar, AB_WARP_BYTES);
#pragma unroll
        for (int h = 0; h < 2; h++) {
            tma_load_3d(sQ + h * 4096, &p.tmQKV, 0, seg * 32, head * 2 + h, bar);
            tma_load_3d(sK + h * 4096, &p.tmQKV, 0, seg * 32, 64 + head * 2 + h, bar);
            tma_load_3d(sV + h * 4096, &p.tmQKV, 0, seg * 32, 128 + head * 2 + h, bar);
            tma_load_3d(sKm + h * 1024, &p.tmKVM, 0, seg * 8, head * 2 + h, bar);
            tma_load_3d(sVm + h * 1024, &p.tmKVM, 0, seg * 8, 64 + head * 2 + h, bar);
        }
    }
    __syncwarp();
    mbar_wait(bar, 0);
    const int lr = lane & 7, lm = lane >> 3;
    float s[2][5][4];
#pragma unroll
    for (int m = 0; m < 2; m++)
#pragma unroll
        for (int n = 0; n < 5; n++)
#pragma unroll
            for (int i = 0; i < 4; i++) s[m][n][i] = 0.f;
#pragma unroll
    for (int kp = 0; kp < 4; kp++) {
        const int hb = kp >> 1, c0 = (kp & 1) * 4;
        uint32_t a[2][2][4];
#pragma unroll
        for (int m = 0; m < 2; m++)
#pragma unroll
            for (int ks = 0; ks < 2; ks++) {
                int row = m * 16 + (lm & 1) * 8 + lr, ch = c0 + ks * 2 + (lm >> 1);
                ldmatrix_x4(a[m][ks][0], a[m][ks][1], a[m][ks][2], a[m][ks][3], sQ + hb * 4096 + row * 128 + ((ch ^ (row & 7)) << 4));
            }
#pragma unroll
        for (int n = 0; n < 5; n++) {
            uint32_t b0, b1, b2, b3;
            int ch = c0 + lm;
            if (n == 0) ldmatrix_x4(b0, b1, b2, b3, sKm + hb * 1024 + lr * 128 + ((ch ^ lr) << 4));
            else { int row = (n - 1) * 8 + lr; ldmatrix_x4(b0, b1, b2, b3, sK + hb * 4096 + row * 128 + ((ch ^ (row & 7)) << 4)); }
#pragma unroll
            for (int m = 0; m < 2; m++) { mma_f(s[m][n], a[m][0], b0, b1); mma_f(s[m][n], a[m][1], b2, b3); }
        }
    }
    const float sc = 0.08838834764831845f * 1.4426950408889634f;
    uint32_t pa[2][3][4];
    float inv[2][2];
#pragma unroll
    for (int m = 0; m < 2; m++) {
        const int r0 = m * 16 + g8, r1 = r0 + 8;
        float mx0 = -3.0e38f, mx1 = -3.0e38f;
#pragma unroll
        for (int n = 0; n < 5; n++) {
            if (n > 0) {
                int j = (n - 1) * 8 + t4 * 2;
                if (j > r0) s[m][n][0] = -3.0e38f;
                if (j + 1 > r0) s[m][n][1] = -3.0e38f;
                if (j > r1) s[m][n][2] = -3.0e38f;
                if (j + 1 > r1) s[m][n][3] = -3.0e38f;
            }
            mx0 = fmaxf(mx0, fmaxf(s[m][n][0], s[m][n][1]));
            mx1 = fmaxf(mx1, fmaxf(s[m][n][2], s[m][n][3]));
        }
        mx0 = fmaxf(mx0, __shfl_xor_sync(0xffffffff, mx0, 1)); mx0 = fmaxf(mx0, __shfl_xor_sync(0xffffffff, mx0, 2));
        mx1 = fmaxf(mx1, __shfl_xor_sync(0xffffffff, mx1, 1)); mx1 = fmaxf(mx1, __shfl_xor_sync(0xffffffff, mx1, 2));
        const float mb0 = mx0 * sc, mb1 = mx1 * sc;
        float l0 = 0.f, l1 = 0.f;
#pragma unroll
        for (int n = 0; n < 5; n++) {
            s[m][n][0] = ex2a(fmaf(s[m][n][0], sc, -mb0)); s[m][n][1] = ex2a(fmaf(s[m][n][1], sc, -mb0));
            s[m][n][2] = ex2a(fmaf(s[m][n][2], sc, -mb1)); s[m][n][3] = ex2a(fmaf(s[m][n][3], sc, -mb1));
            l0 += s[m][n][0] + s[m][n][1]; l1 += s[m][n][2] + s[m][n][3];
        }
        l0 += __shfl_xor_sync(0xffffffff, l0, 1); l0 += __shfl_xor_sync(0xffffffff, l0, 2);
        l1 += __shfl_xor_sync(0xffffffff, l1, 1); l1 += __shfl_xor_sync(0xffffffff, l1, 2);
        inv[m][0] = 1.0f / l0; inv[m][1] = 1.0f / l1;
#pragma unroll
        for (int n = 0; n < 5; n++) {
            pa[m][n >> 1][(n & 1) * 2 + 0] = pack_bf16(s[m][n][0] * inv[m][0], s[m][n][1] * inv[m][0]);
            pa[m][n >> 1][(n & 1) * 2 + 1] = pack_bf16(s[m][n][2] * inv[m][1], s[m][n][3] * inv[m][1]);
        }
        pa[m][2][2] = 0u; pa[m][2][3] = 0u;
    }
    __syncwarp();
#pragma unroll
    for (int dq = 0; dq < 4; dq++) {
        float oc[2][4][4];
#pragma unroll
        for (int m = 0; m < 2; m++)
#pragma unroll
            for (int n = 0; n < 4; n++)
#pragma unroll
                for (int i = 0; i < 4; i++) oc[m][n][i] = 0.f;
        const int hb = dq >> 1, c0 = (dq & 1) * 4;
#pragma unroll
        for (int ks = 0; ks < 3; ks++) {
#pragma unroll
            for (int dp = 0; dp < 2; dp++) {
                int key = ks * 16 + (lm & 1) * 8 + lr, ch = c0 + dp * 2 + (lm >> 1);
                uint32_t addr;
                if (key < 8 || key >= 40) addr = sVm + hb * 1024 + lr * 128 + ((ch ^ lr) << 4);
                else { int row = key - 8; addr = sV + hb * 4096 + row * 128 + ((ch ^ (row & 7)) << 4); }
                uint32_t b0, b1, b2, b3;
                ldmatrix_x4_t(b0, b1, b2, b3, addr);
#pragma unroll
                for (int m = 0; m < 2; m++) { mma_f(oc[m][dp * 2], pa[m][ks], b0, b1); mma_f(oc[m][dp * 2 + 1], pa[m][ks], b2, b3); }
            }
        }
#pragma unroll
        for (int m = 0; m < 2; m++)
#pragma unroll
            for (int dp = 0; dp < 2; dp++) {
                int row = m * 16 + (lm & 1) * 8 + lr, ch = c0 + dp * 2 + (lm >> 1);
                stmatrix_x4(sQ + hb * 4096 + row * 128 + ((ch ^ (row & 7)) << 4),
                            pack_bf16(oc[m][dp * 2][0], oc[m][dp * 2][1]), pack_bf16(oc[m][dp * 2][2], oc[m][dp * 2][3]),
                            pack_bf16(oc[m][dp * 2 + 1][0], oc[m][dp * 2 + 1][1]), pack_bf16(oc[m][dp * 2 + 1][2], oc[m][dp * 2 + 1][3]));
            }
    }
    fence_proxy_async_smem();
    __syncwarp();
    if (lane == 0) {
        tma_store_3d(&p.tmO, sQ, 0, seg * 32, head * 2);
        tma_store_3d(&p.tmO, sQ + 4096, 0, seg * 32, head * 2 + 1);
        bulk_commit();
        bulk_wait_all0();
        fence_proxy_async_all();
        __threadfence();
        atomicAdd(p.tile_flags + (seg >> 2), 1u);
    }
}

struct GemmSParams {
    CUtensorMap tmA;
    CUtensorMap tmB;
    CUtensorMap tmC;
    int n_tiles;
    int kblocks_half;
    int c_col64;
    const unsigned int* tile_flags;
    unsigned int tile_target;
};
constexpr int GS_NST = 5;
constexpr int GS_SMEM = GS_NST * 32768 + 32768 + 256;

__global__ void __launch_bounds__(288, 1) gemm_s_kernel(const __grid_constant__ GemmSParams p) {
    extern __shared__ __align__(1024) unsigned char smem[];
    const uint32_t sS = smem_u32(smem);
    const uint32_t sR = sS + GS_NST * 32768;
    const uint32_t bars = sR + 32768;
    const uint32_t barFull = bars, barEmpty = bars + 8 * GS_NST, barRed = bars + 16 * GS_NST;
    const int warp = __shfl_sync(0xffffffff, threadIdx.x >> 5, 0), lane = threadIdx.x & 31;
    const int tile = blockIdx.x >> 1, kh = blockIdx.x & 1;
    const int mt = tile / p.n_tiles, nt = tile % p.n_tiles;
    if (threadIdx.x == 0) {
        for (int i = 0; i < GS_NST; i++) { mbar_init(barFull + 8 * i, 1); mbar_init(barEmpty + 8 * i, 8); }
        mbar_init(barRed, 1);
        fence_mbar_init();
        mbar_expect_tx(barRed, 32768);
    }
    __syncthreads();
    cluster_sync_all();
    if (warp == 8) {
        if (lane == 0) {
            {
                uint32_t n = 0;
                while (ld_acquire_u32(p.tile_flags + mt) < p.tile_target) { if (++n > (1u << 24)) break; __nanosleep(200); }
                fence_proxy_async_all();
            }
            for (int i = 0; i < p.kblocks_half; i++) {
                int slot = i % GS_NST;
                if (i >= GS_NST) mbar_wait(barEmpty + 8 * slot, ((i / GS_NST) - 1) & 1);
                mbar_expect_tx(barFull + 8 * slot, 32768);
                int kb = kh * p.kblocks_half + i;
                tma_load_3d(sS + slot * 32768, &p.tmA, 0, mt * 128, kb, barFull + 8 * slot);
                tma_load_3d(sS + slot * 32768 + 16384, &p.tmB, 0, kb * 64, nt * 2, barFull + 8 * slot);
            }
        }
    } else {
        const int wg = warp >> 2, wq = warp & 3;
        float acc[64];
        int prev = 0;
        for (int i = 0; i < p.kblocks_half; i++) {
            int slot = i % GS_NST;
            mbar_wait(barFull + 8 * slot, (i / GS_NST) & 1);
            wg_fence();
            uint64_t da = make_desc(sS + slot * 32768 + wg * 8192, 16, 1024);
            uint64_t db = make_desc(sS + slot * 32768 + 16384, 8192, 1024);
#pragma unroll
            for (int kk = 0; kk < 4; kk++)
                wgmma_m64n128k16_ss_tb(acc, da + (uint64_t)(kk * 2), db + (uint64_t)(kk * 128), (i | kk) != 0);
            wg_commit();
            if (i > 0) { wg_wait<1>(); if (lane == 0) mbar_arrive(barEmpty + 8 * prev); }
            prev = slot;
        }
        wg_wait<0>();
        const uint32_t peer = kh ^ 1;
        const uint32_t rbuf = mapa_u32(sR, peer), rbar = mapa_u32(barRed, peer);
        const int tw = threadIdx.x;
#pragma unroll
        for (int j = 0; j < 8; j++) {
            float a[4];
#pragma unroll
            for (int i = 0; i < 4; i++) a[i] = kh == 0 ? acc[(8 + j) * 4 + i] : acc[j * 4 + i];
            st_async_v4(rbuf + (j * 256 + tw) * 16, __float_as_uint(a[0]), __float_as_uint(a[1]), __float_as_uint(a[2]), __float_as_uint(a[3]), rbar);
        }
        mbar_wait(barRed, 0);
        named_bar_sync(1, 256);
        const uint32_t stage = sS + wg * 8192;
        const int mrow = wq * 16 + (lane & 7) + ((lane >> 3) & 1) * 8, mcolh = lane >> 4;
#pragma unroll
        for (int c = 0; c < 4; c++) {
            uint32_t r[4];
#pragma unroll
            for (int e = 0; e < 2; e++) {
                int j = c * 2 + e;
                float4 v;
                asm volatile("ld.shared.v4.f32 {%0,%1,%2,%3}, [%4];" : "=f"(v.x), "=f"(v.y), "=f"(v.z), "=f"(v.w) : "r"(sR + (j * 256 + tw) * 16) : "memory");
                float a[4];
#pragma unroll
                for (int i = 0; i < 4; i++) a[i] = kh == 0 ? acc[j * 4 + i] : acc[(8 + j) * 4 + i];
                r[e * 2 + 0] = pack_bf16(a[0] + v.x, a[1] + v.y);
                r[e * 2 + 1] = pack_bf16(a[2] + v.z, a[3] + v.w);
            }
            int chunk = (c * 2 + mcolh) ^ (mrow & 7);
            stmatrix_x4(stage + mrow * 128 + chunk * 16, r[0], r[1], r[2], r[3]);
        }
        fence_proxy_async_smem();
        named_bar_sync(2 + wg, 128);
        if ((threadIdx.x & 127) == 0) {
            tma_store_3d(&p.tmC, stage, 0, mt * 128 + wg * 64, p.c_col64 + nt * 2 + kh);
            bulk_commit();
            bulk_wait_read0();
        }
    }
    __syncthreads();
    cluster_sync_all();
}

typedef CUresult (*PFN_encodeTiled)(CUtensorMap*, CUtensorMapDataType, cuuint32_t, void*, const cuuint64_t*, const cuuint64_t*,
                                    const cuuint32_t*, const cuuint32_t*, CUtensorMapInterleave, CUtensorMapSwizzle,
                                    CUtensorMapL2promotion, CUtensorMapFloatOOBfill);
static PFN_encodeTiled g_encode = nullptr;
static void init_encode() {
    if (g_encode) return;
    void* fn = nullptr;
    cudaDriverEntryPointQueryResult st;
    cudaGetDriverEntryPoint("cuTensorMapEncodeTiled", &fn, cudaEnableDefault, &st);
    g_encode = (PFN_encodeTiled)fn;
}
static CUtensorMap make_tmap_3d64(const void* ptr, uint64_t rows, uint64_t cols, uint64_t ld, uint32_t box_rows, uint32_t box_c64) {
    CUtensorMap tm;
    cuuint64_t dims[3] = {64, rows, cols / 64};
    cuuint64_t strides[2] = {ld * 2, 128};
    cuuint32_t box[3] = {64, box_rows, box_c64};
    cuuint32_t es[3] = {1, 1, 1};
    g_encode(&tm, CU_TENSOR_MAP_DATA_TYPE_BFLOAT16, 3, (void*)ptr, dims, strides, box, es, CU_TENSOR_MAP_INTERLEAVE_NONE,
             CU_TENSOR_MAP_SWIZZLE_128B, CU_TENSOR_MAP_L2_PROMOTION_L2_128B, CU_TENSOR_MAP_FLOAT_OOB_FILL_NONE);
    return tm;
}

__device__ __align__(1024) bf16 g_qkvA[2048 * 1536];
__device__ __align__(1024) bf16 g_oA[2048 * 512];
__device__ __align__(1024) bf16 g_qkvB[2048 * 12288];
__device__ __align__(1024) bf16 g_kvmem[64 * 8 * 8192];
__device__ __align__(1024) bf16 g_oB[2048 * 4096];
__device__ __align__(1024) float g_part[2 * 64 * 256];
__device__ __align__(128) unsigned int g_flags[192];

__global__ void cleanup_kernel() {
    const int i = blockIdx.x * blockDim.x + threadIdx.x;
    const int n = gridDim.x * blockDim.x;
    uint4 z = make_uint4(0, 0, 0, 0);
    for (int k = i; k < 2 * 64 * 64; k += n) reinterpret_cast<uint4*>(g_part)[k] = z;
    if (i < 192) g_flags[i] = 0u;
}

__global__ void delay_kernel() {}

template <typename T> static T* sym_addr(T& sym) { void* p = nullptr; cudaGetSymbolAddress(&p, sym); return (T*)p; }

extern "C" void kernel_launch(void* const* d_in, const int* in_sizes, int n_in, void* d_out, int out_size) {
    const bf16* A_x = (const bf16*)d_in[0];
    const bf16* A_wqkv = (const bf16*)d_in[1];
    const bf16* A_wo = (const bf16*)d_in[2];
    const bf16* B_x = (const bf16*)d_in[3];
    const bf16* B_mem0 = (const bf16*)d_in[4];
    const bf16* B_Wq = (const bf16*)d_in[5];
    const bf16* B_Wk = (const bf16*)d_in[6];
    const bf16* B_Wv = (const bf16*)d_in[7];
    const bf16* B_Wo = (const bf16*)d_in[8];
    bf16* out = (bf16*)d_out;

    static bool inited = false;
    static cudaStream_t s1, s2;
    static cudaEvent_t e_kv, e_s1, e_ch;
    if (!inited) {
        init_encode();
        cudaFuncSetAttribute(gemm_w_kernel, cudaFuncAttributeMaxDynamicSharedMemorySize, GW_SMEM);
        cudaFuncSetAttribute(gemm_s_kernel, cudaFuncAttributeMaxDynamicSharedMemorySize, GS_SMEM);
        cudaFuncSetAttribute(chain_kernel, cudaFuncAttributeMaxDynamicSharedMemorySize, CH_SMEM);
        cudaFuncSetAttribute(chain_kernel, cudaFuncAttributeNonPortableClusterSizeAllowed, 1);
        cudaFuncSetAttribute(attn_a_kernel, cudaFuncAttributeMaxDynamicSharedMemorySize, AA_SMEM);
        cudaFuncSetAttribute(attn_b_kernel, cudaFuncAttributeMaxDynamicSharedMemorySize, AB_SMEM);
        int plo = 0, phi = 0;
        cudaDeviceGetStreamPriorityRange(&plo, &phi);
        cudaStreamCreateWithPriority(&s1, cudaStreamNonBlocking, plo);
        cudaStreamCreateWithPriority(&s2, cudaStreamNonBlocking, phi);
        cudaEventCreateWithFlags(&e_kv, cudaEventDisableTiming);
        cudaEventCreateWithFlags(&e_s1, cudaEventDisableTiming);
        cudaEventCreateWithFlags(&e_ch, cudaEventDisableTiming);
        inited = true;
    }
    void *qkvA, *oA, *qkvB, *kvmem, *oB, *part, *membuf, *flags;
    cudaGetSymbolAddress(&qkvA, g_qkvA); cudaGetSymbolAddress(&oA, g_oA); cudaGetSymbolAddress(&qkvB, g_qkvB);
    cudaGetSymbolAddress(&kvmem, g_kvmem); cudaGetSymbolAddress(&oB, g_oB); cudaGetSymbolAddress(&part, g_part);
    membuf = nullptr; cudaGetSymbolAddress(&flags, g_flags);
    cudaStream_t s0 = cudaStreamPerThread;

    cudaEventRecord(e_kv, s0);
    cudaStreamWaitEvent(s1, e_kv, 0);
    cudaStreamWaitEvent(s2, e_kv, 0);
    ChainParams pc;
    pc.tmW[0] = make_tmap_3d64(B_Wq, 512, 4096, 4096, 256, 1);
    pc.tmW[1] = make_tmap_3d64(B_Wk, 512, 4096, 4096, 256, 1);
    pc.tmW[2] = make_tmap_3d64(B_Wv, 512, 4096, 4096, 256, 1);
    pc.tmWo = make_tmap_3d64(B_Wo, 4096, 512, 512, 128, 1);
    pc.tmKV = make_tmap_3d64(qkvB, 2048, 12288, 12288, 32, 1);
    pc.mem0 = B_mem0; pc.kvmem = (bf16*)kvmem; pc.part = (float*)part; pc.membuf = (uint4*)membuf;
    pc.flags = (const unsigned int*)flags; pc.flag_target = 128; pc.dbg = nullptr; pc.seg_flags = (unsigned int*)flags + 64;
    {
        cudaLaunchConfig_t cfg = {};
        cfg.gridDim = dim3(64); cfg.blockDim = dim3(384); cfg.dynamicSmemBytes = CH_SMEM; cfg.stream = s2;
        cudaLaunchAttribute at[2];
        at[0].id = cudaLaunchAttributeClusterDimension; at[0].val.clusterDim.x = 16; at[0].val.clusterDim.y = 1; at[0].val.clusterDim.z = 1;
        cfg.attrs = at; cfg.numAttrs = 1;
        cudaLaunchKernelEx(&cfg, chain_kernel, pc);
    }

    cudaEventRecord(e_ch, s2);
    delay_kernel<<<1, 32, 0, s1>>>();
    GemmWParams pkv;
    pkv.tmA = make_tmap_3d64(B_x, 2048, 512, 512, 128, 1);
    pkv.tmB[0] = make_tmap_3d64(B_Wk, 512, 4096, 4096, 64, 2);
    pkv.tmB[1] = make_tmap_3d64(B_Wv, 512, 4096, 4096, 64, 2);
    pkv.tmB[2] = make_tmap_3d64(B_Wq, 512, 4096, 4096, 64, 2);
    pkv.tmC = make_tmap_3d64(qkvB, 2048, 12288, 12288, 128, 1);
    pkv.ntiles_per_mat = 32; pkv.c_col64[0] = 64; pkv.c_col64[1] = 128; pkv.c_col64[2] = 0;
    pkv.m_splits = 1; pkv.mtiles_per_cta = 16; pkv.flag_mats = 2; pkv.flags = (unsigned int*)flags;
    gemm_w_kernel<<<64, 384, GW_SMEM, s1>>>(pkv);

    GemmWParams pq = pkv;
    pq.tmB[0] = pkv.tmB[2]; pq.c_col64[0] = 0; pq.m_splits = 2; pq.mtiles_per_cta = 8; pq.flag_mats = 0; pq.flags = nullptr;
    gemm_w_kernel<<<64, 384, GW_SMEM, s1>>>(pq);

    GemmWParams p1;
    p1.tmA = make_tmap_3d64(A_x, 2048, 512, 512, 128, 1);
    p1.tmB[0] = make_tmap_3d64(A_wqkv, 512, 1536, 1536, 64, 2); p1.tmB[1] = p1.tmB[0]; p1.tmB[2] = p1.tmB[0];
    p1.tmC = make_tmap_3d64(qkvA, 2048, 1536, 1536, 128, 1);
    p1.ntiles_per_mat = 12; p1.c_col64[0] = p1.c_col64[1] = p1.c_col64[2] = 0;
    p1.m_splits = 4; p1.mtiles_per_cta = 4; p1.flag_mats = 0; p1.flags = nullptr;
    gemm_w_kernel<<<48, 384, GW_SMEM, s1>>>(p1);

    AttnAParams pa;
    {
        cuuint64_t dims[2] = {1536, 2048}; cuuint64_t strides[1] = {3072}; cuuint32_t box[2] = {16, AA_KT}; cuuint32_t es[2] = {1, 1};
        g_encode(&pa.tmKV, CU_TENSOR_MAP_DATA_TYPE_BFLOAT16, 2, qkvA, dims, strides, box, es, CU_TENSOR_MAP_INTERLEAVE_NONE,
                 CU_TENSOR_MAP_SWIZZLE_32B, CU_TENSOR_MAP_L2_PROMOTION_L2_128B, CU_TENSOR_MAP_FLOAT_OOB_FILL_NONE);
    }
    pa.qkv = (const bf16*)qkvA; pa.o = (bf16*)oA;
    attn_a_kernel<<<256, 256, AA_SMEM, s1>>>(pa);

    GemmWParams p2;
    p2.tmA = make_tmap_3d64(oA, 2048, 512, 512, 128, 1);
    p2.tmB[0] = make_tmap_3d64(A_wo, 512, 512, 512, 64, 2); p2.tmB[1] = p2.tmB[0]; p2.tmB[2] = p2.tmB[0];
    p2.tmC = make_tmap_3d64(out, 2048, 1024, 1024, 128, 1);
    p2.ntiles_per_mat = 4; p2.c_col64[0] = p2.c_col64[1] = p2.c_col64[2] = 0;
    p2.m_splits = 16; p2.mtiles_per_cta = 1; p2.flag_mats = 0; p2.flags = nullptr;
    gemm_w_kernel<<<64, 384, GW_SMEM, s1>>>(p2);

    AttnBParams pb;
    pb.tmQKV = make_tmap_3d64(qkvB, 2048, 12288, 12288, 32, 1);
    pb.tmKVM = make_tmap_3d64(kvmem, 512, 8192, 8192, 8, 1);
    pb.tmO = make_tmap_3d64(oB, 2048, 4096, 4096, 32, 1);
    pb.seg_flags = (const unsigned int*)flags + 64; pb.seg_target = 256; pb.tile_flags = (unsigned int*)flags + 128;
    attn_b_kernel<<<512, 128, AB_SMEM, s1>>>(pb);

    GemmSParams p4;
    p4.tmA = make_tmap_3d64(oB, 2048, 4096, 4096, 128, 1);
    p4.tmB = make_tmap_3d64(B_Wo, 4096, 512, 512, 64, 2);
    p4.tmC = make_tmap_3d64(out, 2048, 1024, 1024, 64, 1);
    p4.n_tiles = 4; p4.kblocks_half = 32; p4.c_col64 = 8;
    p4.tile_flags = (const unsigned int*)flags + 128; p4.tile_target = 128;
    {
        cudaLaunchConfig_t cfg = {};
        cfg.gridDim = dim3(128); cfg.blockDim = dim3(288); cfg.dynamicSmemBytes = GS_SMEM; cfg.stream = s1;
        cudaLaunchAttribute at[2];
        at[0].id = cudaLaunchAttributeClusterDimension; at[0].val.clusterDim.x = 2; at[0].val.clusterDim.y = 1; at[0].val.clusterDim.z = 1;
        at[1].id = cudaLaunchAttributeProgrammaticStreamSerialization; at[1].val.programmaticStreamSerializationAllowed = 1;
        cfg.attrs = at; cfg.numAttrs = 2;
        cudaLaunchKernelEx(&cfg, gemm_s_kernel, p4);
    }
    cudaEventRecord(e_s1, s1);
    cudaStreamWaitEvent(s0, e_s1, 0);
    cudaStreamWaitEvent(s0, e_ch, 0);
    cleanup_kernel<<<64, 256, 0, s0>>>();
}
```

```cpp
#include <cuda_runtime.h>
#include <cuda_bf16.h>
#include <cuda.h>
#include <stdint.h>

typedef __nv_bfloat16 bf16;

__device__ __forceinline__ uint32_t smem_u32(const void* p) { return (uint32_t)__cvta_generic_to_shared(p); }
__device__ __forceinline__ void mbar_init(uint32_t bar, uint32_t cnt) {
    asm volatile("mbarrier.init.shared::cta.b64 [%0], %1;" :: "r"(bar), "r"(cnt) : "memory");
}
__device__ __forceinline__ void mbar_expect_tx(uint32_t bar, uint32_t bytes) {
    asm volatile("mbarrier.arrive.expect_tx.shared::cta.b64 _, [%0], %1;" :: "r"(bar), "r"(bytes) : "memory");
}
__device__ __forceinline__ void mbar_arrive(uint32_t bar) {
    asm volatile("mbarrier.arrive.shared::cta.b64 _, [%0];" :: "r"(bar) : "memory");
}
__device__ __forceinline__ bool mbar_try_wait(uint32_t bar, uint32_t parity) {
    uint32_t ok;
    asm volatile("{\n.reg .pred p;\nmbarrier.try_wait.parity.shared::cta.b64 p, [%1], %2;\nselp.u32 %0, 1, 0, p;\n}"
                 : "=r"(ok) : "r"(bar), "r"(parity) : "memory");
    return ok != 0;
}
__device__ __forceinline__ void mbar_wait(uint32_t bar, uint32_t parity) {
    uint32_t n = 0;
    while (!mbar_try_wait(bar, parity)) { if (++n > (1u << 20)) break; }
}
__device__ __forceinline__ void fence_proxy_async_smem() { asm volatile("fence.proxy.async.shared::cta;" ::: "memory"); }
__device__ __forceinline__ void fence_proxy_async_all() { asm volatile("fence.proxy.async;" ::: "memory"); }
__device__ __forceinline__ void fence_mbar_init() { asm volatile("fence.mbarrier_init.release.cluster;" ::: "memory"); }

__device__ __forceinline__ void tma_load_3d(uint32_t dst, const CUtensorMap* tm, int c0, int c1, int c2, uint32_t bar) {
    asm volatile("cp.async.bulk.tensor.3d.shared::cluster.global.mbarrier::complete_tx::bytes [%0], [%1, {%3, %4, %5}], [%2];"
                 :: "r"(dst), "l"(tm), "r"(bar), "r"(c0), "r"(c1), "r"(c2) : "memory");
}
__device__ __forceinline__ void tma_load_2d(uint32_t dst, const CUtensorMap* tm, int c0, int c1, uint32_t bar) {
    asm volatile("cp.async.bulk.tensor.2d.shared::cluster.global.mbarrier::complete_tx::bytes [%0], [%1, {%3, %4}], [%2];"
                 :: "r"(dst), "l"(tm), "r"(bar), "r"(c0), "r"(c1) : "memory");
}
__device__ __forceinline__ void tma_store_3d(const CUtensorMap* tm, uint32_t src, int c0, int c1, int c2) {
    asm volatile("cp.async.bulk.tensor.3d.global.shared::cta.bulk_group [%0, {%2, %3, %4}], [%1];"
                 :: "l"(tm), "r"(src), "r"(c0), "r"(c1), "r"(c2) : "memory");
}
__device__ __forceinline__ void bulk_commit() { asm volatile("cp.async.bulk.commit_group;" ::: "memory"); }
__device__ __forceinline__ void bulk_wait_read0() { asm volatile("cp.async.bulk.wait_group.read 0;" ::: "memory"); }
__device__ __forceinline__ void bulk_wait_all0() { asm volatile("cp.async.bulk.wait_group 0;" ::: "memory"); }
__device__ __forceinline__ void prefetch_tmap(const CUtensorMap* tm) {
    asm volatile("prefetch.tensormap [%0];" :: "l"(tm) : "memory");
}

__device__ __forceinline__ void wg_fence() { asm volatile("wgmma.fence.sync.aligned;" ::: "memory"); }
__device__ __forceinline__ void wg_commit() { asm volatile("wgmma.commit_group.sync.aligned;" ::: "memory"); }
template <int N> __device__ __forceinline__ void wg_wait() { asm volatile("wgmma.wait_group.sync.aligned %0;" :: "n"(N) : "memory"); }

__device__ __forceinline__ void named_bar_sync(int id, int nthreads) {
    asm volatile("bar.sync %0, %1;" :: "r"(id), "r"(nthreads) : "memory");
}
__device__ __forceinline__ void named_bar_arrive(int id, int nthreads) {
    asm volatile("bar.arrive %0, %1;" :: "r"(id), "r"(nthreads) : "memory");
}

__device__ __forceinline__ uint64_t make_desc(uint32_t saddr, uint32_t lbo_bytes, uint32_t sbo_bytes) {
    return (uint64_t)((saddr & 0x3FFFF) >> 4) | ((uint64_t)(lbo_bytes >> 4) << 16) | ((uint64_t)(sbo_bytes >> 4) << 32) | ((uint64_t)1 << 62);
}

__device__ __forceinline__ uint32_t pack_bf16(float lo, float hi) {
    uint32_t r;
    asm("cvt.rn.bf16x2.f32 %0, %1, %2;" : "=r"(r) : "f"(hi), "f"(lo));
    return r;
}
__device__ __forceinline__ void stmatrix_x4(uint32_t addr, uint32_t r0, uint32_t r1, uint32_t r2, uint32_t r3) {
    asm volatile("stmatrix.sync.aligned.m8n8.x4.shared.b16 [%0], {%1,%2,%3,%4};" :: "r"(addr), "r"(r0), "r"(r1), "r"(r2), "r"(r3) : "memory");
}
__device__ __forceinline__ void ldmatrix_x4(uint32_t& r0, uint32_t& r1, uint32_t& r2, uint32_t& r3, uint32_t addr) {
    asm volatile("ldmatrix.sync.aligned.m8n8.x4.shared.b16 {%0,%1,%2,%3}, [%4];" : "=r"(r0), "=r"(r1), "=r"(r2), "=r"(r3) : "r"(addr) : "memory");
}
__device__ __forceinline__ void ldmatrix_x4_t(uint32_t& r0, uint32_t& r1, uint32_t& r2, uint32_t& r3, uint32_t addr) {
    asm volatile("ldmatrix.sync.aligned.m8n8.x4.trans.shared.b16 {%0,%1,%2,%3}, [%4];" : "=r"(r0), "=r"(r1), "=r"(r2), "=r"(r3) : "r"(addr) : "memory");
}
__device__ __forceinline__ void ldmatrix_x2(uint32_t& r0, uint32_t& r1, uint32_t addr) {
    asm volatile("ldmatrix.sync.aligned.m8n8.x2.shared.b16 {%0,%1}, [%2];" : "=r"(r0), "=r"(r1) : "r"(addr) : "memory");
}
__device__ __forceinline__ void ldmatrix_x2_t(uint32_t& r0, uint32_t& r1, uint32_t addr) {
    asm volatile("ldmatrix.sync.aligned.m8n8.x2.trans.shared.b16 {%0,%1}, [%2];" : "=r"(r0), "=r"(r1) : "r"(addr) : "memory");
}
__device__ __forceinline__ void mma16816(float* c, const uint32_t* a, uint32_t b0, uint32_t b1) {
    asm volatile("mma.sync.aligned.m16n8k16.row.col.f32.bf16.bf16.f32 {%0,%1,%2,%3}, {%4,%5,%6,%7}, {%8,%9}, {%0,%1,%2,%3};"
                 : "+f"(c[0]), "+f"(c[1]), "+f"(c[2]), "+f"(c[3]) : "r"(a[0]), "r"(a[1]), "r"(a[2]), "r"(a[3]), "r"(b0), "r"(b1));
}

__device__ __forceinline__ void wgmma_m64n128k16_ss_tb(float* d, uint64_t da, uint64_t db, int scale_d) {
    asm volatile(
        "{\n.reg .pred p;\nsetp.ne.b32 p, %66, 0;\n"
        "wgmma.mma_async.sync.aligned.m64n128k16.f32.bf16.bf16 "
        "{%0,%1,%2,%3,%4,%5,%6,%7,%8,%9,%10,%11,%12,%13,%14,%15,"
        "%16,%17,%18,%19,%20,%21,%22,%23,%24,%25,%26,%27,%28,%29,%30,%31,"
        "%32,%33,%34,%35,%36,%37,%38,%39,%40,%41,%42,%43,%44,%45,%46,%47,"
        "%48,%49,%50,%51,%52,%53,%54,%55,%56,%57,%58,%59,%60,%61,%62,%63},"
        " %64, %65, p, 1, 1, 0, 1;\n}\n"
        : "+f"(d[0]), "+f"(d[1]), "+f"(d[2]), "+f"(d[3]), "+f"(d[4]), "+f"(d[5]), "+f"(d[6]), "+f"(d[7]),
          "+f"(d[8]), "+f"(d[9]), "+f"(d[10]), "+f"(d[11]), "+f"(d[12]), "+f"(d[13]), "+f"(d[14]), "+f"(d[15]),
          "+f"(d[16]), "+f"(d[17]), "+f"(d[18]), "+f"(d[19]), "+f"(d[20]), "+f"(d[21]), "+f"(d[22]), "+f"(d[23]),
          "+f"(d[24]), "+f"(d[25]), "+f"(d[26]), "+f"(d[27]), "+f"(d[28]), "+f"(d[29]), "+f"(d[30]), "+f"(d[31]),
          "+f"(d[32]), "+f"(d[33]), "+f"(d[34]), "+f"(d[35]), "+f"(d[36]), "+f"(d[37]), "+f"(d[38]), "+f"(d[39]),
          "+f"(d[40]), "+f"(d[41]), "+f"(d[42]), "+f"(d[43]), "+f"(d[44]), "+f"(d[45]), "+f"(d[46]), "+f"(d[47]),
          "+f"(d[48]), "+f"(d[49]), "+f"(d[50]), "+f"(d[51]), "+f"(d[52]), "+f"(d[53]), "+f"(d[54]), "+f"(d[55]),
          "+f"(d[56]), "+f"(d[57]), "+f"(d[58]), "+f"(d[59]), "+f"(d[60]), "+f"(d[61]), "+f"(d[62]), "+f"(d[63])
        : "l"(da), "l"(db), "r"(scale_d));
}

__device__ __forceinline__ void wgmma_m64n128k16_rs(float* d, const uint32_t* a, uint64_t db, int scale_d) {
    asm volatile(
        "{\n.reg .pred p;\nsetp.ne.b32 p, %69, 0;\n"
        "wgmma.mma_async.sync.aligned.m64n128k16.f32.bf16.bf16 "
        "{%0,%1,%2,%3,%4,%5,%6,%7,%8,%9,%10,%11,%12,%13,%14,%15,"
        "%16,%17,%18,%19,%20,%21,%22,%23,%24,%25,%26,%27,%28,%29,%30,%31,"
        "%32,%33,%34,%35,%36,%37,%38,%39,%40,%41,%42,%43,%44,%45,%46,%47,"
        "%48,%49,%50,%51,%52,%53,%54,%55,%56,%57,%58,%59,%60,%61,%62,%63},"
        " {%64,%65,%66,%67}, %68, p, 1, 1, 0;\n}\n"
        : "+f"(d[0]), "+f"(d[1]), "+f"(d[2]), "+f"(d[3]), "+f"(d[4]), "+f"(d[5]), "+f"(d[6]), "+f"(d[7]),
          "+f"(d[8]), "+f"(d[9]), "+f"(d[10]), "+f"(d[11]), "+f"(d[12]), "+f"(d[13]), "+f"(d[14]), "+f"(d[15]),
          "+f"(d[16]), "+f"(d[17]), "+f"(d[18]), "+f"(d[19]), "+f"(d[20]), "+f"(d[21]), "+f"(d[22]), "+f"(d[23]),
          "+f"(d[24]), "+f"(d[25]), "+f"(d[26]), "+f"(d[27]), "+f"(d[28]), "+f"(d[29]), "+f"(d[30]), "+f"(d[31]),
          "+f"(d[32]), "+f"(d[33]), "+f"(d[34]), "+f"(d[35]), "+f"(d[36]), "+f"(d[37]), "+f"(d[38]), "+f"(d[39]),
          "+f"(d[40]), "+f"(d[41]), "+f"(d[42]), "+f"(d[43]), "+f"(d[44]), "+f"(d[45]), "+f"(d[46]), "+f"(d[47]),
          "+f"(d[48]), "+f"(d[49]), "+f"(d[50]), "+f"(d[51]), "+f"(d[52]), "+f"(d[53]), "+f"(d[54]), "+f"(d[55]),
          "+f"(d[56]), "+f"(d[57]), "+f"(d[58]), "+f"(d[59]), "+f"(d[60]), "+f"(d[61]), "+f"(d[62]), "+f"(d[63])
        : "r"(a[0]), "r"(a[1]), "r"(a[2]), "r"(a[3]), "l"(db), "r"(scale_d));
}
__device__ __forceinline__ void stmatrix_x4_t(uint32_t addr, uint32_t r0, uint32_t r1, uint32_t r2, uint32_t r3) {
    asm volatile("stmatrix.sync.aligned.m8n8.x4.trans.shared.b16 [%0], {%1,%2,%3,%4};" :: "r"(addr), "r"(r0), "r"(r1), "r"(r2), "r"(r3) : "memory");
}
template <int R> __device__ __forceinline__ void reg_alloc() { asm volatile("setmaxnreg.inc.sync.aligned.u32 %0;" :: "n"(R)); }
template <int R> __device__ __forceinline__ void reg_dealloc() { asm volatile("setmaxnreg.dec.sync.aligned.u32 %0;" :: "n"(R)); }

struct GemmWParams {
    CUtensorMap tmA;
    CUtensorMap tmB[3];
    CUtensorMap tmC;
    int ntiles_per_mat;
    int c_col64[3];
    int m_splits;
    int mtiles_per_cta;
    int flag_mats;
    unsigned int* flags;
};

constexpr int GW_NST = 11;
constexpr int GW_SMEM = GW_NST * 16384 + 32768 + 256;

__global__ void __launch_bounds__(384, 1) gemm_w_kernel(const __grid_constant__ GemmWParams p) {
    extern __shared__ __align__(1024) unsigned char smem[];
    const uint32_t sA = smem_u32(smem);
    const uint32_t sOut = sA + GW_NST * 16384;
    const uint32_t bars = sOut + 32768;
    const uint32_t barFull = bars, barEmpty = bars + 8 * GW_NST;
    const int warp = __shfl_sync(0xffffffff, threadIdx.x >> 5, 0), lane = threadIdx.x & 31;

    const int gnt = blockIdx.x / p.m_splits;
    const int ms = blockIdx.x % p.m_splits;
    const int mat = gnt / p.ntiles_per_mat;
    const int nt = gnt % p.ntiles_per_mat;
    const int tile0 = ms * p.mtiles_per_cta;
    const int ntl = p.mtiles_per_cta;

    if (threadIdx.x == 0) {
        for (int i = 0; i < GW_NST; i++) { mbar_init(barFull + 8 * i, 1); mbar_init(barEmpty + 8 * i, 8); }
        fence_mbar_init();
    }
    __syncthreads();

    const int wgi = __shfl_sync(0xffffffff, threadIdx.x >> 7, 0);
    if (wgi == 0) {
        reg_dealloc<40>();
        if (warp == 0 && lane == 0) {
            const CUtensorMap* tmB = &p.tmB[mat];
            const int total = 8 + ntl * 8;
            for (int idx = 0; idx < total; idx++) {
                int slot = idx % GW_NST;
                if (idx >= GW_NST) mbar_wait(barEmpty + 8 * slot, ((idx / GW_NST) - 1) & 1);
                mbar_expect_tx(barFull + 8 * slot, 16384);
                if (idx < 8) tma_load_3d(sA + slot * 16384, tmB, 0, idx * 64, nt * 2, barFull + 8 * slot);
                else {
                    int t = (idx - 8) >> 3, j = (idx - 8) & 7;
                    tma_load_3d(sA + slot * 16384, &p.tmA, 0, (tile0 + t) * 128, j, barFull + 8 * slot);
                }
            }
        }
    } else {
        reg_alloc<232>();
        const int wg = (warp >> 2) - 1, wq = warp & 3;
        uint32_t w[32][4];
        float acc[64];
        {
            const int krow = (lane & 7) + ((lane >> 4) & 1) * 8;
            const int chunk = wq * 2 + ((lane >> 3) & 1);
#pragma unroll
            for (int kb = 0; kb < 8; kb++) {
                mbar_wait(barFull + 8 * kb, 0);
#pragma unroll
                for (int kk = 0; kk < 4; kk++) {
                    int r = kk * 16 + krow;
                    uint32_t addr = sA + kb * 16384 + wg * 8192 + r * 128 + ((chunk ^ (r & 7)) << 4);
                    ldmatrix_x4_t(w[kb * 4 + kk][0], w[kb * 4 + kk][1], w[kb * 4 + kk][2], w[kb * 4 + kk][3], addr);
                }
                __syncwarp();
                if (lane == 0) mbar_arrive(barEmpty + 8 * kb);
            }
        }
        const bool do_flag = (p.flags != nullptr) && (mat < p.flag_mats);
        const int tid_wg = threadIdx.x & 127;
        int pend_tile = -1;
        int idx = 8;
        for (int t = 0; t < ntl; t++) {
            int prev_slot = 0;
            if (wg == 0) { if (t > 0) named_bar_sync(3, 256); }
            else named_bar_sync(4, 256);
#pragma unroll
            for (int j = 0; j < 8; j++, idx++) {
                int slot = idx % GW_NST;
                mbar_wait(barFull + 8 * slot, (idx / GW_NST) & 1);
                wg_fence();
                uint64_t db = make_desc(sA + slot * 16384, 16, 1024);
#pragma unroll
                for (int kk = 0; kk < 4; kk++)
                    wgmma_m64n128k16_rs(acc, w[j * 4 + kk], db + (uint64_t)(kk * 2), (j | kk) != 0);
                wg_commit();
                if (j == 7) {
                    if (wg == 0) named_bar_arrive(4, 256);
                    else if (t + 1 < ntl) named_bar_arrive(3, 256);
                }
                if (j > 0) {
                    wg_wait<1>();
                    if (lane == 0) mbar_arrive(barEmpty + 8 * prev_slot);
                }
                prev_slot = slot;
            }
            wg_wait<0>();
            if (lane == 0) mbar_arrive(barEmpty + 8 * prev_slot);
            if (tid_wg == 0 && pend_tile >= 0) {
                if (do_flag) {
                    bulk_wait_all0();
                    fence_proxy_async_all();
                    __threadfence();
                    atomicAdd(p.flags + pend_tile, 1u);
                } else bulk_wait_read0();
            }
            named_bar_sync(1 + wg, 128);
            const uint32_t sbase = sOut + wg * 16384;
            const int mid = lane >> 3;
            const int chunk = wq * 2 + (mid & 1);
#pragma unroll
            for (int nb = 0; nb < 8; nb++) {
                const int a0 = nb * 8;
                uint32_t r0 = pack_bf16(acc[a0 + 0], acc[a0 + 1]);
                uint32_t r1 = pack_bf16(acc[a0 + 2], acc[a0 + 3]);
                uint32_t r2 = pack_bf16(acc[a0 + 4], acc[a0 + 5]);
                uint32_t r3 = pack_bf16(acc[a0 + 6], acc[a0 + 7]);
                int tok = nb * 16 + (mid >> 1) * 8 + (lane & 7);
                stmatrix_x4_t(sbase + tok * 128 + ((chunk ^ (tok & 7)) << 4), r0, r1, r2, r3);
            }
            fence_proxy_async_smem();
            named_bar_sync(1 + wg, 128);
            if (tid_wg == 0) {
                tma_store_3d(&p.tmC, sbase, 0, (tile0 + t) * 128, p.c_col64[mat] + nt * 2 + wg);
                bulk_commit();
            }
            pend_tile = tile0 + t;
        }
        if (pend_tile >= 0 && tid_wg == 0) {
            bulk_wait_all0();
            if (do_flag) {
                fence_proxy_async_all();
                __threadfence();
                atomicAdd(p.flags + pend_tile, 1u);
            }
        }
    }
}

#define PACE 0
#define NSTEPS 64
#define POLL_B 1
#define POLL_R 1
struct ChainParams {
    CUtensorMap tmW[3];
    CUtensorMap tmWo;
    CUtensorMap tmKV;
    const bf16* mem0;
    bf16* kvmem;
    float* part;
    uint4* membuf;
    const unsigned int* flags;
    unsigned int flag_target;
    unsigned int* seg_flags;
    long long* dbg;
};

constexpr int CH_MEM_STRIDE = 1040;
constexpr int CH_Q_STRIDE = 144;
constexpr int CH_O_STRIDE = 272;
constexpr int CH_NKV = 4;
constexpr int CH_KV_BYTES = 15360;
constexpr int CH_OFF_WO = 0;
constexpr int CH_OFF_WV = 65536;
constexpr int CH_OFF_KV = 131072;
constexpr int CH_OFF_MEM = CH_OFF_KV + CH_NKV * CH_KV_BYTES;
constexpr int CH_OFF_RS = CH_OFF_MEM + 8192;
constexpr int CH_OFF_STG = CH_OFF_RS + 8192;
constexpr int CH_OFF_Q = CH_OFF_STG + 512;
constexpr int CH_OFF_O = CH_OFF_Q + 1152;
constexpr int CH_OFF_RED1 = CH_OFF_O + 2176;
constexpr int CH_OFF_SC = CH_OFF_RED1 + 6144;
constexpr int CH_OFF_RED2 = CH_OFF_SC + 1280;
constexpr int CH_OFF_ZERO = CH_OFF_RED2 + 2048;
constexpr int CH_OFF_BAR = CH_OFF_ZERO + 128;
constexpr int CH_OFF_TS = CH_OFF_BAR + 256;
constexpr int CH_SMEM = CH_OFF_TS + 1024;

__device__ __forceinline__ uint32_t mapa_u32(uint32_t addr, uint32_t rank) {
    uint32_t r; asm volatile("mapa.shared::cluster.u32 %0, %1, %2;" : "=r"(r) : "r"(addr), "r"(rank)); return r;
}
__device__ __forceinline__ void st_async_v4(uint32_t addr, uint32_t a, uint32_t b, uint32_t c, uint32_t d, uint32_t mbar) {
    asm volatile("st.async.shared::cluster.mbarrier::complete_tx::bytes.v4.b32 [%0], {%1,%2,%3,%4}, [%5];"
                 :: "r"(addr), "r"(a), "r"(b), "r"(c), "r"(d), "r"(mbar) : "memory");
}
__device__ __forceinline__ void st_async_v2(uint32_t addr, uint32_t a, uint32_t b, uint32_t mbar) {
    asm volatile("st.async.shared::cluster.mbarrier::complete_tx::bytes.v2.b32 [%0], {%1,%2}, [%3];"
                 :: "r"(addr), "r"(a), "r"(b), "r"(mbar) : "memory");
}
__device__ __forceinline__ bool mbar_try_wait_cl(uint32_t bar, uint32_t parity) {
    uint32_t ok;
    asm volatile("{\n.reg .pred p;\nmbarrier.try_wait.parity.acquire.cluster.shared::cta.b64 p, [%1], %2;\nselp.u32 %0, 1, 0, p;\n}"
                 : "=r"(ok) : "r"(bar), "r"(parity) : "memory");
    return ok != 0;
}
__device__ __forceinline__ void mbar_wait_cl(uint32_t bar, uint32_t parity) {
    uint32_t n = 0;
    while (!mbar_try_wait_cl(bar, parity)) { if (++n > (1u << 20)) break; }
}
__device__ __forceinline__ void cluster_sync_all() {
    asm volatile("barrier.cluster.arrive.aligned;\nbarrier.cluster.wait.aligned;" ::: "memory");
}
__device__ __forceinline__ uint4 ld_relaxed_v4(const void* p) {
    uint4 v;
    asm volatile("ld.relaxed.gpu.global.v4.u32 {%0,%1,%2,%3}, [%4];" : "=r"(v.x), "=r"(v.y), "=r"(v.z), "=r"(v.w) : "l"(p) : "memory");
    return v;
}
__device__ __forceinline__ void st_relaxed_v4(void* p, uint32_t a, uint32_t b, uint32_t c, uint32_t d) {
    asm volatile("st.relaxed.gpu.global.v4.u32 [%0], {%1,%2,%3,%4};" :: "l"(p), "r"(a), "r"(b), "r"(c), "r"(d) : "memory");
}
__device__ __forceinline__ unsigned int ld_acquire_u32(const unsigned int* p) {
    unsigned int v;
    asm volatile("ld.acquire.gpu.global.u32 %0, [%1];" : "=r"(v) : "l"(p) : "memory");
    return v;
}
__device__ __forceinline__ void lds128(uint32_t* r, uint32_t addr) {
    asm volatile("ld.shared.v4.u32 {%0,%1,%2,%3}, [%4];" : "=r"(r[0]), "=r"(r[1]), "=r"(r[2]), "=r"(r[3]) : "r"(addr) : "memory");
}
__device__ __forceinline__ float ex2_approx(float x) { float y; asm("ex2.approx.ftz.f32 %0, %1;" : "=f"(y) : "f"(x)); return y; }
__device__ __forceinline__ void mma_nv(float* c, const uint32_t* a, uint32_t b0, uint32_t b1) {
    asm("mma.sync.aligned.m16n8k16.row.col.f32.bf16.bf16.f32 {%0,%1,%2,%3}, {%4,%5,%6,%7}, {%8,%9}, {%0,%1,%2,%3};"
        : "+f"(c[0]), "+f"(c[1]), "+f"(c[2]), "+f"(c[3]) : "r"(a[0]), "r"(a[1]), "r"(a[2]), "r"(a[3]), "r"(b0), "r"(b1));
}

__device__ __forceinline__ void st_relaxed_v2(void* p, uint32_t a, uint32_t b) {
    asm volatile("st.relaxed.gpu.global.v2.u32 [%0], {%1,%2};" :: "l"(p), "r"(a), "r"(b) : "memory");
}

#define TSX(i)
__global__ void __launch_bounds__(384, 1) chain_kernel(const __grid_constant__ ChainParams p) {
    extern __shared__ __align__(1024) unsigned char smem[];
    const uint32_t sb = smem_u32(smem);
    int tid; asm volatile("mov.u32 %0, %%tid.x;" : "=r"(tid));
    int bid; asm volatile("mov.u32 %0, %%ctaid.x;" : "=r"(bid));
    const int lane = tid & 31;
    const int warp = __shfl_sync(0xffffffff, tid >> 5, 0);
    const int wgi = __shfl_sync(0xffffffff, tid >> 7, 0);
    const int rank = bid & 15, cl = bid >> 4;
    const int head = bid >> 1, half = bid & 1;
    const uint32_t barSc = sb + CH_OFF_BAR, barV = barSc + 8, barLd = barSc + 16, barKV = barSc + 24, barMem = barKV + 8 * CH_NKV, barRS = barMem + 8;

    if (tid == 0) {
        mbar_init(barSc, 1); mbar_init(barV, 1); mbar_init(barLd, 1); mbar_init(barMem, 1); mbar_init(barRS, 1);
        for (int i = 0; i < CH_NKV; i++) mbar_init(barKV + 8 * i, 1);
        fence_mbar_init();
        mbar_expect_tx(barSc, 1280);
        mbar_expect_tx(barV, 1024);
        mbar_expect_tx(barMem, 8192);
        mbar_expect_tx(barRS, 4096);
    }
    if (tid < 32) *reinterpret_cast<uint32_t*>(smem + CH_OFF_ZERO + tid * 4) = 0u;
    __syncthreads();
    cluster_sync_all();
    const uint32_t peer = rank ^ 1;
    const int t4 = lane & 3, g8 = lane >> 2;
    const int lr = lane & 7, lm = lane >> 3;

    if (wgi < 2) {
        reg_alloc<208>();
        const int g = warp >> 1, kh = warp & 1;
        uint32_t wqk[2][16][4];
        {
            const int c64 = head * 2 + half;
            const int krow = lr + ((lane >> 4) & 1) * 8;
            const int chunk = g * 2 + (lm & 1);
            if (tid == 0) {
                mbar_expect_tx(barLd, 131072);
                tma_load_3d(sb + CH_OFF_WO, &p.tmW[0], 0, 0, c64, barLd);
                tma_load_3d(sb + CH_OFF_WO + 32768, &p.tmW[0], 0, 256, c64, barLd);
                tma_load_3d(sb + CH_OFF_WV, &p.tmW[1], 0, 0, c64, barLd);
                tma_load_3d(sb + CH_OFF_WV + 32768, &p.tmW[1], 0, 256, c64, barLd);
            }
            mbar_wait(barLd, 0);
#pragma unroll
            for (int m = 0; m < 2; m++)
#pragma unroll
                for (int ks = 0; ks < 16; ks++) {
                    int r = kh * 256 + ks * 16 + krow;
                    uint32_t addr = sb + (m == 0 ? CH_OFF_WO : CH_OFF_WV) + r * 128 + ((chunk ^ (r & 7)) << 4);
                    ldmatrix_x4_t(wqk[m][ks][0], wqk[m][ks][1], wqk[m][ks][2], wqk[m][ks][3], addr);
                }
            named_bar_sync(7, 256);
            if (tid == 0) {
                mbar_expect_tx(barLd, 131072);
                tma_load_3d(sb + CH_OFF_WV, &p.tmW[2], 0, 0, c64, barLd);
                tma_load_3d(sb + CH_OFF_WV + 32768, &p.tmW[2], 0, 256, c64, barLd);
                for (int i = 0; i < 4; i++) tma_load_3d(sb + CH_OFF_WO + i * 16384, &p.tmWo, 0, head * 128, half * 4 + i, barLd);
            }
            mbar_wait(barLd, 1);
            uint32_t f[16][4];
#pragma unroll
            for (int ks = 0; ks < 16; ks++) {
                int r = kh * 256 + ks * 16 + krow;
                ldmatrix_x4_t(f[ks][0], f[ks][1], f[ks][2], f[ks][3], sb + CH_OFF_WV + r * 128 + ((chunk ^ (r & 7)) << 4));
            }
            named_bar_sync(7, 256);
#pragma unroll
            for (int ks = 0; ks < 16; ks++)
                asm volatile("st.shared.v4.u32 [%0], {%1,%2,%3,%4};" :: "r"(sb + CH_OFF_WV + ((warp * 16 + ks) * 32 + lane) * 16), "r"(f[ks][0]), "r"(f[ks][1]), "r"(f[ks][2]), "r"(f[ks][3]) : "memory");
#pragma unroll
            for (int ks = 0; ks < 8; ks++)
#pragma unroll
                for (int mt = 0; mt < 2; mt++) {
                    int r = ks * 16 + krow;
                    int colchunk = warp * 4 + mt * 2 + (lm & 1);
                    ldmatrix_x4_t(f[ks * 2 + mt][0], f[ks * 2 + mt][1], f[ks * 2 + mt][2], f[ks * 2 + mt][3],
                                  sb + CH_OFF_WO + (colchunk >> 3) * 16384 + r * 128 + (((colchunk & 7) ^ (r & 7)) << 4));
                }
            named_bar_sync(7, 256);
#pragma unroll
            for (int i = 0; i < 16; i++)
                asm volatile("st.shared.v4.u32 [%0], {%1,%2,%3,%4};" :: "r"(sb + CH_OFF_WO + ((warp * 16 + i) * 32 + lane) * 16), "r"(f[i][0]), "r"(f[i][1]), "r"(f[i][2]), "r"(f[i][3]) : "memory");
            named_bar_sync(7, 256);
        }
        const uint32_t wvbase = sb + CH_OFF_WV + (warp * 16 * 32 + lane) * 16;
        const uint32_t wobase = sb + CH_OFF_WO + (warp * 16 * 32 + lane) * 16;
        const uint32_t bAddr = sb + CH_OFF_MEM + kh * 4096 + lr * 64 + ((lm ^ ((lr >> 1) & 3)) << 4);
        const uint32_t redMine = sb + CH_OFF_RED1 + warp * 512 + lane * 16, redOther = sb + CH_OFF_RED1 + (warp ^ 1) * 512 + lane * 16;
        const uint32_t redMineV = sb + CH_OFF_RED1 + 4096 + warp * 256 + lane * 8, redOtherV = sb + CH_OFF_RED1 + 4096 + (warp ^ 1) * 256 + lane * 8;
        const uint32_t qDst = sb + CH_OFF_Q + lr * CH_Q_STRIDE + (g * 16 + (lm & 1) * 8) * 2;
        const uint32_t kvOff = lr * 128 + (((g * 2 + (lm & 1)) ^ lr) << 4);
        const uint32_t peerBase = mapa_u32(sb, peer) - sb;
        const uint32_t oAddr = sb + CH_OFF_O + lr * CH_O_STRIDE + lm * 16;
        const uint32_t rsDst = mapa_u32(sb + CH_OFF_RS + (rank >> 1) * 512 + lane * 16, warp * 2 + half);
        const uint32_t rsBar = mapa_u32(barRS, warp * 2 + half);
        float* llW = p.part + ((size_t)(cl * 16 + rank) * 64 + tid) * 4;
        for (int s = 0; s < NSTEPS; s++) {
            const uint32_t sKV = sb + CH_OFF_KV + (s & (CH_NKV - 1)) * CH_KV_BYTES;
            uint32_t wo[16][4], wv[2][2][4];
#pragma unroll
            for (int i = 0; i < 8; i++) lds128(wo[i], wobase + i * 512);
            lds128(wv[0][0], wvbase); lds128(wv[0][1], wvbase + 512);
            TSX(0);
            if (s == 0) {
                for (int i = tid; i < 512; i += 256) {
                    int tok = i & 7, c = i >> 3;
                    uint4 v = *reinterpret_cast<const uint4*>(p.mem0 + tok * 512 + c * 8);
                    *reinterpret_cast<uint4*>(smem + CH_OFF_MEM + (c >> 2) * 512 + tok * 64 + (((c & 3) ^ ((tok >> 1) & 3)) << 4)) = v;
                }
                named_bar_sync(7, 256);
            } else {
                mbar_wait(barMem, (s - 1) & 1);
                if (tid == 0) mbar_expect_tx(barMem, 8192);
            }
            TSX(1);
            {
                float aq[4], ak[4], av[4];
#pragma unroll
                for (int i = 0; i < 4; i++) { aq[i] = ak[i] = av[i] = 0.f; }
                uint32_t b[2][4];
                ldmatrix_x4(b[0][0], b[0][1], b[0][2], b[0][3], bAddr);
#pragma unroll
                for (int kk = 0; kk < 8; kk++) {
                    if (kk + 1 < 8) {
                        ldmatrix_x4(b[(kk + 1) & 1][0], b[(kk + 1) & 1][1], b[(kk + 1) & 1][2], b[(kk + 1) & 1][3], bAddr + (kk + 1) * 512);
                        lds128(wv[(kk + 1) & 1][0], wvbase + (2 * kk + 2) * 512);
                        lds128(wv[(kk + 1) & 1][1], wvbase + (2 * kk + 3) * 512);
                    }
                    mma_nv(aq, wqk[0][2 * kk], b[kk & 1][0], b[kk & 1][1]);
                    mma_nv(ak, wqk[1][2 * kk], b[kk & 1][0], b[kk & 1][1]);
                    mma_nv(av, wv[kk & 1][0], b[kk & 1][0], b[kk & 1][1]);
                    mma_nv(aq, wqk[0][2 * kk + 1], b[kk & 1][2], b[kk & 1][3]);
                    mma_nv(ak, wqk[1][2 * kk + 1], b[kk & 1][2], b[kk & 1][3]);
                    mma_nv(av, wv[kk & 1][1], b[kk & 1][2], b[kk & 1][3]);
                }
                TSX(2);
                float gv[6], kp[6];
#pragma unroll
                for (int i = 0; i < 4; i++) {
                    gv[i] = kh == 0 ? ak[i] : aq[i];
                    kp[i] = kh == 0 ? aq[i] : ak[i];
                }
                gv[4] = kh == 0 ? av[2] : av[0]; gv[5] = kh == 0 ? av[3] : av[1];
                kp[4] = kh == 0 ? av[0] : av[2]; kp[5] = kh == 0 ? av[1] : av[3];
                asm volatile("st.shared.v4.f32 [%0], {%1,%2,%3,%4};" :: "r"(redMine), "f"(gv[0]), "f"(gv[1]), "f"(gv[2]), "f"(gv[3]) : "memory");
                asm volatile("st.shared.v2.f32 [%0], {%1,%2};" :: "r"(redMineV), "f"(gv[4]), "f"(gv[5]) : "memory");
                named_bar_sync(1 + g, 64);
                float o0, o1, o2, o3, o4, o5;
                asm volatile("ld.shared.v4.f32 {%0,%1,%2,%3}, [%4];" : "=f"(o0), "=f"(o1), "=f"(o2), "=f"(o3) : "r"(redOther) : "memory");
                asm volatile("ld.shared.v2.f32 {%0,%1}, [%2];" : "=f"(o4), "=f"(o5) : "r"(redOtherV) : "memory");
                uint32_t r0 = pack_bf16(kp[0] + o0, kp[1] + o1);
                uint32_t r1 = pack_bf16(kp[2] + o2, kp[3] + o3);
                uint32_t r2 = pack_bf16(kp[4] + o4, kp[5] + o5);
                asm volatile("stmatrix.sync.aligned.m8n8.x2.trans.shared.b16 [%0], {%1,%2};" :: "r"(kh == 0 ? qDst : sKV + kvOff), "r"(r0), "r"(r1) : "memory");
                const uint32_t vAddr = sKV + 5120 + half * 5120 + lr * 128 + (((g * 2 + kh) ^ lr) << 4);
                asm volatile("stmatrix.sync.aligned.m8n8.x1.trans.shared.b16 [%0], {%1};" :: "r"(vAddr), "r"(r2) : "memory");
                named_bar_arrive(5, 384);
                TSX(3);
                __syncwarp();
                if (lane < 8) {
                    uint32_t f[4];
                    lds128(f, vAddr);
                    st_async_v4(vAddr + peerBase, f[0], f[1], f[2], f[3], barV + peerBase);
                }
            }
            if (s == NSTEPS - 1) break;
            named_bar_sync(10, 384);
#pragma unroll
            for (int i = 8; i < 16; i++) {
                lds128(wo[i], wobase + i * 512);
            }
            TSX(4);
            named_bar_sync(8, 384);
            TSX(5);
            const uint32_t tag = ((s >> 1) + 1) & 1;
            const uint32_t slotOff = (s & 1) * (64 * 256);
            {
                float a2[2][2][4];
#pragma unroll
                for (int i = 0; i < 4; i++) { a2[0][0][i] = a2[0][1][i] = a2[1][0][i] = a2[1][1][i] = 0.f; }
                uint32_t b[4][4];
#pragma unroll
                for (int kk = 0; kk < 4; kk++) ldmatrix_x4(b[kk][0], b[kk][1], b[kk][2], b[kk][3], oAddr + kk * 64);
#pragma unroll
                for (int kk = 0; kk < 4; kk++) {
                    mma_nv(a2[0][0], wo[kk * 4 + 0], b[kk][0], b[kk][1]);
                    mma_nv(a2[1][0], wo[kk * 4 + 1], b[kk][0], b[kk][1]);
                    mma_nv(a2[0][1], wo[kk * 4 + 2], b[kk][2], b[kk][3]);
                    mma_nv(a2[1][1], wo[kk * 4 + 3], b[kk][2], b[kk][3]);
                }
                st_async_v4(rsDst, pack_bf16(a2[0][0][0] + a2[0][1][0], a2[0][0][1] + a2[0][1][1]), pack_bf16(a2[0][0][2] + a2[0][1][2], a2[0][0][3] + a2[0][1][3]),
                            pack_bf16(a2[1][0][0] + a2[1][1][0], a2[1][0][1] + a2[1][1][1]), pack_bf16(a2[1][0][2] + a2[1][1][2], a2[1][0][3] + a2[1][1][3]), rsBar);
            }
            TSX(6);
            if (warp < 2) {
                mbar_wait(barRS, s & 1);
                TSX(7);
                uint32_t u[8][2];
#pragma unroll
                for (int h = 0; h < 8; h++)
                    asm volatile("ld.shared.v2.u32 {%0,%1}, [%2];" : "=r"(u[h][0]), "=r"(u[h][1]) : "r"(sb + CH_OFF_RS + h * 512 + lane * 16 + warp * 8) : "memory");
                if (tid == 0) mbar_expect_tx(barRS, 4096);
                float f0 = 0.f, f1 = 0.f, f2 = 0.f, f3 = 0.f;
                {
                    float a[8], b[8], c[8], d[8];
#pragma unroll
                    for (int h = 0; h < 8; h++) {
                        a[h] = __uint_as_float(u[h][0] << 16); b[h] = __uint_as_float(u[h][0] & 0xffff0000u);
                        c[h] = __uint_as_float(u[h][1] << 16); d[h] = __uint_as_float(u[h][1] & 0xffff0000u);
                    }
                    f0 = ((a[0] + a[1]) + (a[2] + a[3])) + ((a[4] + a[5]) + (a[6] + a[7]));
                    f1 = ((b[0] + b[1]) + (b[2] + b[3])) + ((b[4] + b[5]) + (b[6] + b[7]));
                    f2 = ((c[0] + c[1]) + (c[2] + c[3])) + ((c[4] + c[5]) + (c[6] + c[7]));
                    f3 = ((d[0] + d[1]) + (d[2] + d[3])) + ((d[4] + d[5]) + (d[6] + d[7]));
                }
                const uint32_t x0 = (__float_as_uint(f0) & ~1u) | tag;
                st_relaxed_v4(llW + slotOff, x0, __float_as_uint(f1), __float_as_uint(f2), __float_as_uint(f3));
                const float* r1 = p.part + slotOff + ((size_t)((cl ^ 1) * 16 + rank) * 64 + tid) * 4;
                const float* r2 = p.part + slotOff + ((size_t)((cl ^ 2) * 16 + rank) * 64 + tid) * 4;
                const float* r3 = p.part + slotOff + ((size_t)((cl ^ 3) * 16 + rank) * 64 + tid) * 4;
                uint4 v1, v2, v3;
                uint32_t n = 0;
                do { v1 = ld_relaxed_v4(r1); v2 = ld_relaxed_v4(r2); v3 = ld_relaxed_v4(r3); }
                while (POLL_R && (((v1.x ^ tag) | (v2.x ^ tag) | (v3.x ^ tag)) & 1u) && ++n < (1u << 22));
                TSX(8);
                f0 = (__uint_as_float(x0) + __uint_as_float(v1.x)) + (__uint_as_float(v2.x) + __uint_as_float(v3.x));
                f1 = (f1 + __uint_as_float(v1.y)) + (__uint_as_float(v2.y) + __uint_as_float(v3.y));
                f2 = (f2 + __uint_as_float(v1.z)) + (__uint_as_float(v2.z) + __uint_as_float(v3.z));
                f3 = (f3 + __uint_as_float(v1.w)) + (__uint_as_float(v2.w) + __uint_as_float(v3.w));
                const int ch = warp * 2 + (lm & 1);
                asm volatile("stmatrix.sync.aligned.m8n8.x2.trans.shared.b16 [%0], {%1,%2};"
                             :: "r"(sb + CH_OFF_STG + lr * 64 + ((ch ^ ((lr >> 1) & 3)) << 4)), "r"(pack_bf16(f0, f1)), "r"(pack_bf16(f2, f3)) : "memory");
                named_bar_sync(9, 64);
                uint32_t f[4];
                lds128(f, sb + CH_OFF_STG + lane * 16);
                const uint32_t dst0 = sb + CH_OFF_MEM + (half * 8 + (rank >> 1)) * 512 + lane * 16;
#pragma unroll
                for (int d = 0; d < 8; d++) {
                    const uint32_t dr = warp * 8 + d;
                    st_async_v4(mapa_u32(dst0, dr), f[0], f[1], f[2], f[3], mapa_u32(barMem, dr));
                }
                TSX(9);
            }
        }
    } else {
        reg_dealloc<88>();
        const int aw = warp - 8;
        const uint32_t peerBase = mapa_u32(sb, peer) - sb;
        const float sm_scale = 0.08838834764831845f * 1.4426950408889634f;
        const int kc64 = 64 + head * 2 + half, vc64 = 128 + head * 2;
        auto issue_kv = [&](int s) {
            if ((s & 3) == 0) {
                uint32_t n = 0;
                while (ld_acquire_u32(p.flags + (s >> 2)) < p.flag_target) { if (++n > (1u << 22)) break; }
                fence_proxy_async_all();
            }
            int st = s & (CH_NKV - 1);
            uint32_t base = sb + CH_OFF_KV + st * CH_KV_BYTES;
            mbar_expect_tx(barKV + 8 * st, 12288);
            tma_load_3d(base + 1024, &p.tmKV, 0, s * 32, kc64, barKV + 8 * st);
            tma_load_3d(base + 5120 + 1024, &p.tmKV, 0, s * 32, vc64, barKV + 8 * st);
            tma_load_3d(base + 10240 + 1024, &p.tmKV, 0, s * 32, vc64 + 1, barKV + 8 * st);
        };
        if (aw == 3 && lane == 0) { for (int s = 0; s < CH_NKV - 1; s++) issue_kv(s); }
        const uint32_t kOff0 = lr * 128 + ((lm ^ lr) << 4), kOff1 = lr * 128 + (((4 + lm) ^ lr) << 4);
        const uint32_t qAddr = (lm & 1) ? (sb + CH_OFF_ZERO) : (sb + CH_OFF_Q + lr * CH_Q_STRIDE + (lm >> 1) * 16);
        const uint32_t qStep = (lm & 1) ? 0u : 32u;
        const uint32_t vRow = ((lm >> 1) * 8 + lr) * 128;
        const uint32_t vOff0 = 5120 + (aw >> 1) * 5120 + vRow + ((((aw & 1) * 4 + (lm & 1)) ^ lr) << 4);
        const uint32_t vOff1 = 5120 + (aw >> 1) * 5120 + vRow + ((((aw & 1) * 4 + 2 + (lm & 1)) ^ lr) << 4);
        const uint32_t padAdj = (lm >> 1) ? 2048u : 0u;
        const uint32_t scAddr = sb + CH_OFF_SC + lane * 8;
        const uint32_t oDst = sb + CH_OFF_O + lr * CH_O_STRIDE + (aw * 32 + lm * 8) * 2;
        const int si = tid - 256, sw = si >> 6, stok = (si >> 3) & 7, scn = si & 7;
        const uint32_t kvmOff = (sw == 0 ? 0u : 5120u + half * 5120u) + stok * 128 + ((scn ^ stok) << 4);
        bf16* kvmDst = p.kvmem + (size_t)stok * 8192 + sw * 4096 + head * 128 + half * 64 + scn * 8;
        const bool leader = (tid == 256);
        for (int s = 0; s < NSTEPS; s++) {
            const uint32_t par = s & 1;
            const int st = s & (CH_NKV - 1);
            const uint32_t sKV = sb + CH_OFF_KV + st * CH_KV_BYTES;
            mbar_wait(barKV + 8 * st, (s / CH_NKV) & 1);
            uint32_t kb[2][4][4], va[3][2][4];
#pragma unroll
            for (int n = 0; n < 4; n++) {
                ldmatrix_x4(kb[0][n][0], kb[0][n][1], kb[0][n][2], kb[0][n][3], sKV + (n + 1) * 1024 + kOff0);
                ldmatrix_x4(kb[1][n][0], kb[1][n][1], kb[1][n][2], kb[1][n][3], sKV + (n + 1) * 1024 + kOff1);
            }
            TSX(0);
            named_bar_sync(5, 384);
            TSX(1);
            float sc[5][4];
#pragma unroll
            for (int n = 0; n < 5; n++) { sc[n][0] = sc[n][1] = sc[n][2] = sc[n][3] = 0.f; }
            {
                uint32_t a[4][4], km[2][4];
#pragma unroll
                for (int k = 0; k < 4; k++) ldmatrix_x4(a[k][0], a[k][1], a[k][2], a[k][3], qAddr + k * qStep);
                ldmatrix_x4(km[0][0], km[0][1], km[0][2], km[0][3], sKV + kOff0);
                ldmatrix_x4(km[1][0], km[1][1], km[1][2], km[1][3], sKV + kOff1);
#pragma unroll
                for (int kp = 0; kp < 2; kp++) {
#pragma unroll
                    for (int n = 0; n < 4; n++) mma_nv(sc[n + 1], a[kp * 2], kb[kp][n][0], kb[kp][n][1]);
#pragma unroll
                    for (int n = 0; n < 4; n++) mma_nv(sc[n + 1], a[kp * 2 + 1], kb[kp][n][2], kb[kp][n][3]);
                }
                mma_nv(sc[0], a[0], km[0][0], km[0][1]);
                mma_nv(sc[0], a[1], km[0][2], km[0][3]);
                mma_nv(sc[0], a[2], km[1][0], km[1][1]);
                mma_nv(sc[0], a[3], km[1][2], km[1][3]);
            }
            TSX(2);
            if (aw == 0) {
#pragma unroll
                for (int n = 0; n < 5; n++) st_async_v2(scAddr + peerBase + n * 256, __float_as_uint(sc[n][0]), __float_as_uint(sc[n][1]), barSc + peerBase);
            }
#pragma unroll
            for (int ks = 1; ks < 3; ks++) {
                const uint32_t adj = ks == 2 ? padAdj : 0u;
                ldmatrix_x4_t(va[ks][0][0], va[ks][0][1], va[ks][0][2], va[ks][0][3], sKV + ks * 2048 + vOff0 - adj);
                ldmatrix_x4_t(va[ks][1][0], va[ks][1][1], va[ks][1][2], va[ks][1][3], sKV + ks * 2048 + vOff1 - adj);
            }
            uint4 kvm;
            if (s < NSTEPS - 1) named_bar_arrive(10, 384);
            if (sw == 0) asm volatile("ld.shared.v4.u32 {%0,%1,%2,%3}, [%4];" : "=r"(kvm.x), "=r"(kvm.y), "=r"(kvm.z), "=r"(kvm.w) : "r"(sKV + kvmOff) : "memory");
            TSX(3);
            mbar_wait(barSc, par);
            TSX(4);
            float pp[5][2];
#pragma unroll
            for (int n = 0; n < 5; n++)
                asm volatile("ld.shared.v2.f32 {%0,%1}, [%2];" : "=f"(pp[n][0]), "=f"(pp[n][1]) : "r"(scAddr + n * 256) : "memory");
            if (leader) mbar_expect_tx(barSc, 1280);
#pragma unroll
            for (int n = 0; n < 5; n++) { sc[n][0] += pp[n][0]; sc[n][1] += pp[n][1]; }
            float mx = fmaxf(fmaxf(fmaxf(sc[0][0], sc[0][1]), fmaxf(sc[1][0], sc[1][1])), fmaxf(fmaxf(sc[2][0], sc[2][1]), fmaxf(sc[3][0], sc[3][1])));
            mx = fmaxf(mx, fmaxf(sc[4][0], sc[4][1]));
            mx = fmaxf(mx, __shfl_xor_sync(0xffffffff, mx, 1));
            mx = fmaxf(mx, __shfl_xor_sync(0xffffffff, mx, 2));
            const float mb = mx * sm_scale;
            uint32_t pb[5];
#pragma unroll
            for (int n = 0; n < 5; n++)
                pb[n] = pack_bf16(ex2_approx(fmaf(sc[n][0], sm_scale, -mb)), ex2_approx(fmaf(sc[n][1], sm_scale, -mb)));
            TSX(5);
            float oc[2][4];
#pragma unroll
            for (int i = 0; i < 4; i++) { oc[0][i] = oc[1][i] = 0.f; }
            mma_nv(oc[0], va[1][0], pb[2], pb[3]);
            mma_nv(oc[1], va[1][1], pb[2], pb[3]);
            mma_nv(oc[0], va[2][0], pb[4], 0u);
            mma_nv(oc[1], va[2][1], pb[4], 0u);
            float sm[4] = {0.f, 0.f, 0.f, 0.f};
            {
                const uint32_t ones[4] = {0x3F803F80u, 0x3F803F80u, 0x3F803F80u, 0x3F803F80u};
                mma_nv(sm, ones, pb[0], pb[1]);
                mma_nv(sm, ones, pb[2], pb[3]);
                mma_nv(sm, ones, pb[4], 0u);
            }
            const float i0 = __fdividef(1.0f, sm[0]), i1 = __fdividef(1.0f, sm[1]);
            TSX(6);
            mbar_wait(barV, par);
            TSX(7);
            ldmatrix_x4_t(va[0][0][0], va[0][0][1], va[0][0][2], va[0][0][3], sKV + vOff0);
            ldmatrix_x4_t(va[0][1][0], va[0][1][1], va[0][1][2], va[0][1][3], sKV + vOff1);
            if (leader) mbar_expect_tx(barV, 1024);
            if (sw == 1) asm volatile("ld.shared.v4.u32 {%0,%1,%2,%3}, [%4];" : "=r"(kvm.x), "=r"(kvm.y), "=r"(kvm.z), "=r"(kvm.w) : "r"(sKV + kvmOff) : "memory");
            mma_nv(oc[0], va[0][0], pb[0], pb[1]);
            mma_nv(oc[1], va[0][1], pb[0], pb[1]);
            stmatrix_x4_t(oDst, pack_bf16(oc[0][0] * i0, oc[0][1] * i1), pack_bf16(oc[0][2] * i0, oc[0][3] * i1),
                          pack_bf16(oc[1][0] * i0, oc[1][1] * i1), pack_bf16(oc[1][2] * i0, oc[1][3] * i1));
            if (s < NSTEPS - 1) named_bar_arrive(8, 384);
            TSX(8);
            *reinterpret_cast<uint4*>(kvmDst + (size_t)s * 65536) = kvm;
            if (p.seg_flags) { __syncwarp(); if (lane == 0) { __threadfence(); atomicAdd(p.seg_flags + s, 1u); } }
            if (aw == 3 && lane == 0 && s + CH_NKV - 1 < NSTEPS) issue_kv(s + CH_NKV - 1);
        }
    }
    __syncthreads();
    cluster_sync_all();
}

struct AttnAParams {
    CUtensorMap tmKV;
    const bf16* qkv;
    bf16* o;
};
constexpr int AA_KT = 256;
constexpr int AA_NST = 3;
constexpr int AA_SMEM = AA_NST * 2 * AA_KT * 32 + 64;

__device__ __forceinline__ float ex2a(float x) { float y; asm("ex2.approx.ftz.f32 %0, %1;" : "=f"(y) : "f"(x)); return y; }
__device__ __forceinline__ void mma_f(float* c, const uint32_t* a, uint32_t b0, uint32_t b1) {
    asm("mma.sync.aligned.m16n8k16.row.col.f32.bf16.bf16.f32 {%0,%1,%2,%3}, {%4,%5,%6,%7}, {%8,%9}, {%0,%1,%2,%3};"
        : "+f"(c[0]), "+f"(c[1]), "+f"(c[2]), "+f"(c[3]) : "r"(a[0]), "r"(a[1]), "r"(a[2]), "r"(a[3]), "r"(b0), "r"(b1));
}

__global__ void __launch_bounds__(256, 2) attn_a_kernel(const __grid_constant__ AttnAParams p) {
    extern __shared__ __align__(1024) unsigned char smem[];
    const uint32_t sb = smem_u32(smem);
    const uint32_t bars = sb + AA_NST * 2 * AA_KT * 32;
    const int tid = threadIdx.x, lane = tid & 31, warp = tid >> 5;
    const int head = blockIdx.x >> 3, qt = blockIdx.x & 7;
    const int t4 = lane & 3, g8 = lane >> 2;
    constexpr int NT = 2048 / AA_KT;

    if (tid == 0) {
        for (int i = 0; i < AA_NST; i++) { mbar_init(bars + 8 * i, 1); mbar_init(bars + 8 * (AA_NST + i), 8); }
        fence_mbar_init();
    }
    __syncthreads();
    auto issue = [&](int t) {
        int st = t % AA_NST;
        uint32_t dst = sb + st * (2 * AA_KT * 32);
        mbar_expect_tx(bars + 8 * st, 2 * AA_KT * 32);
        tma_load_2d(dst, &p.tmKV, 512 + head * 16, t * AA_KT, bars + 8 * st);
        tma_load_2d(dst + AA_KT * 32, &p.tmKV, 1024 + head * 16, t * AA_KT, bars + 8 * st);
    };
    if (tid == 0) { for (int t = 0; t < AA_NST; t++) issue(t); }

    uint32_t qa[2][4];
    const int row0 = qt * 256 + warp * 32;
#pragma unroll
    for (int m = 0; m < 2; m++) {
        const bf16* q = p.qkv + (size_t)(row0 + m * 16 + g8) * 1536 + head * 16 + t4 * 2;
        qa[m][0] = *reinterpret_cast<const uint32_t*>(q);
        qa[m][1] = *reinterpret_cast<const uint32_t*>(q + 8 * 1536);
        qa[m][2] = *reinterpret_cast<const uint32_t*>(q + 8);
        qa[m][3] = *reinterpret_cast<const uint32_t*>(q + 8 * 1536 + 8);
    }
    const float sc = 0.25f * 1.4426950408889634f;
    float mrow[2][2], oacc[2][2][4], lacc[2][4];
#pragma unroll
    for (int m = 0; m < 2; m++) {
        mrow[m][0] = mrow[m][1] = -3.0e38f;
#pragma unroll
        for (int i = 0; i < 4; i++) { oacc[m][0][i] = oacc[m][1][i] = 0.f; lacc[m][i] = 0.f; }
    }
    const uint32_t ones = 0x3F803F80u;
    const int lr = lane & 7, lm = lane >> 3;
    const int krow = (lm >> 1) * 8 + lr, kch = lm & 1;
    const uint32_t koff = krow * 32 + ((kch ^ ((krow >> 2) & 1)) << 4);
    const int vrow = (lm & 1) * 8 + lr, vch = lm >> 1;
    const uint32_t voff = vrow * 32 + ((vch ^ ((vrow >> 2) & 1)) << 4);

    for (int t = 0; t < NT; t++) {
        const int st = t % AA_NST;
        mbar_wait(bars + 8 * st, (t / AA_NST) & 1);
        const uint32_t sK = sb + st * (2 * AA_KT * 32), sV = sK + AA_KT * 32;
#pragma unroll 1
        for (int kb = 0; kb < AA_KT / 64; kb++) {
            float s[2][8][4];
#pragma unroll
            for (int np = 0; np < 4; np++) {
                uint32_t b0, b1, b2, b3;
                ldmatrix_x4(b0, b1, b2, b3, sK + (kb * 64 + np * 16) * 32 + koff);
#pragma unroll
                for (int m = 0; m < 2; m++) {
#pragma unroll
                    for (int i = 0; i < 4; i++) { s[m][np * 2][i] = 0.f; s[m][np * 2 + 1][i] = 0.f; }
                    mma_f(s[m][np * 2], qa[m], b0, b1);
                    mma_f(s[m][np * 2 + 1], qa[m], b2, b3);
                }
            }
            uint32_t pa[2][4][4];
#pragma unroll
            for (int m = 0; m < 2; m++) {
                float mx0 = s[m][0][0], mx1 = s[m][0][2];
#pragma unroll
                for (int n = 0; n < 8; n++) {
                    mx0 = fmaxf(mx0, fmaxf(s[m][n][0], s[m][n][1]));
                    mx1 = fmaxf(mx1, fmaxf(s[m][n][2], s[m][n][3]));
                }
                mx0 = fmaxf(mx0, __shfl_xor_sync(0xffffffff, mx0, 1)); mx0 = fmaxf(mx0, __shfl_xor_sync(0xffffffff, mx0, 2));
                mx1 = fmaxf(mx1, __shfl_xor_sync(0xffffffff, mx1, 1)); mx1 = fmaxf(mx1, __shfl_xor_sync(0xffffffff, mx1, 2));
                const float mn0 = fmaxf(mrow[m][0], mx0), mn1 = fmaxf(mrow[m][1], mx1);
                const float a0 = ex2a((mrow[m][0] - mn0) * sc), a1 = ex2a((mrow[m][1] - mn1) * sc);
                mrow[m][0] = mn0; mrow[m][1] = mn1;
                const float mb0 = mn0 * sc, mb1 = mn1 * sc;
#pragma unroll
                for (int d = 0; d < 2; d++) { oacc[m][d][0] *= a0; oacc[m][d][1] *= a0; oacc[m][d][2] *= a1; oacc[m][d][3] *= a1; }
                lacc[m][0] *= a0; lacc[m][2] *= a1;
#pragma unroll
                for (int n = 0; n < 8; n++) {
                    float p0 = ex2a(fmaf(s[m][n][0], sc, -mb0)), p1 = ex2a(fmaf(s[m][n][1], sc, -mb0));
                    float p2 = ex2a(fmaf(s[m][n][2], sc, -mb1)), p3 = ex2a(fmaf(s[m][n][3], sc, -mb1));
                    pa[m][n >> 1][(n & 1) * 2 + 0] = pack_bf16(p0, p1);
                    pa[m][n >> 1][(n & 1) * 2 + 1] = pack_bf16(p2, p3);
                }
            }
#pragma unroll
            for (int ks = 0; ks < 4; ks++) {
                uint32_t b0, b1, b2, b3;
                ldmatrix_x4_t(b0, b1, b2, b3, sV + (kb * 64 + ks * 16) * 32 + voff);
#pragma unroll
                for (int m = 0; m < 2; m++) {
                    mma_f(oacc[m][0], pa[m][ks], b0, b1);
                    mma_f(oacc[m][1], pa[m][ks], b2, b3);
                    mma_f(lacc[m], pa[m][ks], ones, ones);
                }
            }
        }
        __syncwarp();
        if (lane == 0) mbar_arrive(bars + 8 * (AA_NST + st));
        if (tid == 0 && t + AA_NST < NT) {
            mbar_wait(bars + 8 * (AA_NST + st), (t / AA_NST) & 1);
            issue(t + AA_NST);
        }
    }
#pragma unroll
    for (int m = 0; m < 2; m++) {
        const float i0 = 1.0f / lacc[m][0], i1 = 1.0f / lacc[m][2];
        bf16* o = p.o + (size_t)(row0 + m * 16 + g8) * 512 + head * 16 + t4 * 2;
#pragma unroll
        for (int d = 0; d < 2; d++) {
            *reinterpret_cast<uint32_t*>(o + d * 8) = pack_bf16(oacc[m][d][0] * i0, oacc[m][d][1] * i0);
            *reinterpret_cast<uint32_t*>(o + 8 * 512 + d * 8) = pack_bf16(oacc[m][d][2] * i1, oacc[m][d][3] * i1);
        }
    }
}

struct AttnBParams {
    CUtensorMap tmQKV;
    CUtensorMap tmKVM;
    CUtensorMap tmO;
    const unsigned int* seg_flags;
    unsigned int seg_target;
    unsigned int* tile_flags;
};
constexpr int AB_WARP_BYTES = 28672;
constexpr int AB_SMEM = 4 * AB_WARP_BYTES + 64;

__global__ void __launch_bounds__(128, 2) attn_b_kernel(const __grid_constant__ AttnBParams p) {
    extern __shared__ __align__(1024) unsigned char smem[];
    const int tid = threadIdx.x, lane = tid & 31, warp = tid >> 5;
    const uint32_t sb = smem_u32(smem) + warp * AB_WARP_BYTES;
    const uint32_t bar = smem_u32(smem) + 4 * AB_WARP_BYTES + warp * 8;
    asm volatile("griddepcontrol.launch_dependents;" ::: "memory");
    const int seg = blockIdx.x >> 3, head = (blockIdx.x & 7) * 4 + warp;
    const int t4 = lane & 3, g8 = lane >> 2;
    const uint32_t sQ = sb, sK = sb + 8192, sV = sb + 16384, sKm = sb + 24576, sVm = sb + 26624;
    if (lane == 0) {
        mbar_init(bar, 1);
        fence_mbar_init();
        if (p.seg_flags) {
            uint32_t n = 0;
            while (ld_acquire_u32(p.seg_flags + seg) < p.seg_target) { if (++n > (1u << 24)) break; __nanosleep(200); }
            fence_proxy_async_all();
        }
        mbar_expect_tx(bar, AB_WARP_BYTES);
#pragma unroll
        for (int h = 0; h < 2; h++) {
            tma_load_3d(sQ + h * 4096, &p.tmQKV, 0, seg * 32, head * 2 + h, bar);
            tma_load_3d(sK + h * 4096, &p.tmQKV, 0, seg * 32, 64 + head * 2 + h, bar);
            tma_load_3d(sV + h * 4096, &p.tmQKV, 0, seg * 32, 128 + head * 2 + h, bar);
            tma_load_3d(sKm + h * 1024, &p.tmKVM, 0, seg * 8, head * 2 + h, bar);
            tma_load_3d(sVm + h * 1024, &p.tmKVM, 0, seg * 8, 64 + head * 2 + h, bar);
        }
    }
    __syncwarp();
    mbar_wait(bar, 0);
    const int lr = lane & 7, lm = lane >> 3;
    float s[2][5][4];
#pragma unroll
    for (int m = 0; m < 2; m++)
#pragma unroll
        for (int n = 0; n < 5; n++)
#pragma unroll
            for (int i = 0; i < 4; i++) s[m][n][i] = 0.f;
#pragma unroll
    for (int kp = 0; kp < 4; kp++) {
        const int hb = kp >> 1, c0 = (kp & 1) * 4;
        uint32_t a[2][2][4];
#pragma unroll
        for (int m = 0; m < 2; m++)
#pragma unroll
            for (int ks = 0; ks < 2; ks++) {
                int row = m * 16 + (lm & 1) * 8 + lr, ch = c0 + ks * 2 + (lm >> 1);
                ldmatrix_x4(a[m][ks][0], a[m][ks][1], a[m][ks][2], a[m][ks][3], sQ + hb * 4096 + row * 128 + ((ch ^ (row & 7)) << 4));
            }
#pragma unroll
        for (int n = 0; n < 5; n++) {
            uint32_t b0, b1, b2, b3;
            int ch = c0 + lm;
            if (n == 0) ldmatrix_x4(b0, b1, b2, b3, sKm + hb * 1024 + lr * 128 + ((ch ^ lr) << 4));
            else { int row = (n - 1) * 8 + lr; ldmatrix_x4(b0, b1, b2, b3, sK + hb * 4096 + row * 128 + ((ch ^ (row & 7)) << 4)); }
#pragma unroll
            for (int m = 0; m < 2; m++) { mma_f(s[m][n], a[m][0], b0, b1); mma_f(s[m][n], a[m][1], b2, b3); }
        }
    }
    const float sc = 0.08838834764831845f * 1.4426950408889634f;
    uint32_t pa[2][3][4];
    float inv[2][2];
#pragma unroll
    for (int m = 0; m < 2; m++) {
        const int r0 = m * 16 + g8, r1 = r0 + 8;
        float mx0 = -3.0e38f, mx1 = -3.0e38f;
#pragma unroll
        for (int n = 0; n < 5; n++) {
            if (n > 0) {
                int j = (n - 1) * 8 + t4 * 2;
                if (j > r0) s[m][n][0] = -3.0e38f;
                if (j + 1 > r0) s[m][n][1] = -3.0e38f;
                if (j > r1) s[m][n][2] = -3.0e38f;
                if (j + 1 > r1) s[m][n][3] = -3.0e38f;
            }
            mx0 = fmaxf(mx0, fmaxf(s[m][n][0], s[m][n][1]));
            mx1 = fmaxf(mx1, fmaxf(s[m][n][2], s[m][n][3]));
        }
        mx0 = fmaxf(mx0, __shfl_xor_sync(0xffffffff, mx0, 1)); mx0 = fmaxf(mx0, __shfl_xor_sync(0xffffffff, mx0, 2));
        mx1 = fmaxf(mx1, __shfl_xor_sync(0xffffffff, mx1, 1)); mx1 = fmaxf(mx1, __shfl_xor_sync(0xffffffff, mx1, 2));
        const float mb0 = mx0 * sc, mb1 = mx1 * sc;
        float l0 = 0.f, l1 = 0.f;
#pragma unroll
        for (int n = 0; n < 5; n++) {
            s[m][n][0] = ex2a(fmaf(s[m][n][0], sc, -mb0)); s[m][n][1] = ex2a(fmaf(s[m][n][1], sc, -mb0));
            s[m][n][2] = ex2a(fmaf(s[m][n][2], sc, -mb1)); s[m][n][3] = ex2a(fmaf(s[m][n][3], sc, -mb1));
            l0 += s[m][n][0] + s[m][n][1]; l1 += s[m][n][2] + s[m][n][3];
        }
        l0 += __shfl_xor_sync(0xffffffff, l0, 1); l0 += __shfl_xor_sync(0xffffffff, l0, 2);
        l1 += __shfl_xor_sync(0xffffffff, l1, 1); l1 += __shfl_xor_sync(0xffffffff, l1, 2);
        inv[m][0] = 1.0f / l0; inv[m][1] = 1.0f / l1;
#pragma unroll
        for (int n = 0; n < 5; n++) {
            pa[m][n >> 1][(n & 1) * 2 + 0] = pack_bf16(s[m][n][0] * inv[m][0], s[m][n][1] * inv[m][0]);
            pa[m][n >> 1][(n & 1) * 2 + 1] = pack_bf16(s[m][n][2] * inv[m][1], s[m][n][3] * inv[m][1]);
        }
        pa[m][2][2] = 0u; pa[m][2][3] = 0u;
    }
    __syncwarp();
#pragma unroll
    for (int dq = 0; dq < 4; dq++) {
        float oc[2][4][4];
#pragma unroll
        for (int m = 0; m < 2; m++)
#pragma unroll
            for (int n = 0; n < 4; n++)
#pragma unroll
                for (int i = 0; i < 4; i++) oc[m][n][i] = 0.f;
        const int hb = dq >> 1, c0 = (dq & 1) * 4;
#pragma unroll
        for (int ks = 0; ks < 3; ks++) {
#pragma unroll
            for (int dp = 0; dp < 2; dp++) {
                int key = ks * 16 + (lm & 1) * 8 + lr, ch = c0 + dp * 2 + (lm >> 1);
                uint32_t addr;
                if (key < 8 || key >= 40) addr = sVm + hb * 1024 + lr * 128 + ((ch ^ lr) << 4);
                else { int row = key - 8; addr = sV + hb * 4096 + row * 128 + ((ch ^ (row & 7)) << 4); }
                uint32_t b0, b1, b2, b3;
                ldmatrix_x4_t(b0, b1, b2, b3, addr);
#pragma unroll
                for (int m = 0; m < 2; m++) { mma_f(oc[m][dp * 2], pa[m][ks], b0, b1); mma_f(oc[m][dp * 2 + 1], pa[m][ks], b2, b3); }
            }
        }
#pragma unroll
        for (int m = 0; m < 2; m++)
#pragma unroll
            for (int dp = 0; dp < 2; dp++) {
                int row = m * 16 + (lm & 1) * 8 + lr, ch = c0 + dp * 2 + (lm >> 1);
                stmatrix_x4(sQ + hb * 4096 + row * 128 + ((ch ^ (row & 7)) << 4),
                            pack_bf16(oc[m][dp * 2][0], oc[m][dp * 2][1]), pack_bf16(oc[m][dp * 2][2], oc[m][dp * 2][3]),
                            pack_bf16(oc[m][dp * 2 + 1][0], oc[m][dp * 2 + 1][1]), pack_bf16(oc[m][dp * 2 + 1][2], oc[m][dp * 2 + 1][3]));
            }
    }
    fence_proxy_async_smem();
    __syncwarp();
    if (lane == 0) {
        tma_store_3d(&p.tmO, sQ, 0, seg * 32, head * 2);
        tma_store_3d(&p.tmO, sQ + 4096, 0, seg * 32, head * 2 + 1);
        bulk_commit();
        bulk_wait_all0();
        fence_proxy_async_all();
        __threadfence();
        atomicAdd(p.tile_flags + (seg >> 2), 1u);
    }
}

struct GemmSParams {
    CUtensorMap tmA;
    CUtensorMap tmB;
    CUtensorMap tmC;
    int n_tiles;
    int kblocks_half;
    int c_col64;
    const unsigned int* tile_flags;
    unsigned int tile_target;
};
constexpr int GS_NST = 5;
constexpr int GS_SMEM = GS_NST * 32768 + 32768 + 256;

__global__ void __launch_bounds__(288, 1) gemm_s_kernel(const __grid_constant__ GemmSParams p) {
    extern __shared__ __align__(1024) unsigned char smem[];
    const uint32_t sS = smem_u32(smem);
    const uint32_t sR = sS + GS_NST * 32768;
    const uint32_t bars = sR + 32768;
    const uint32_t barFull = bars, barEmpty = bars + 8 * GS_NST, barRed = bars + 16 * GS_NST;
    const int warp = __shfl_sync(0xffffffff, threadIdx.x >> 5, 0), lane = threadIdx.x & 31;
    const int tile = blockIdx.x >> 1, kh = blockIdx.x & 1;
    const int mt = tile / p.n_tiles, nt = tile % p.n_tiles;
    if (threadIdx.x == 0) {
        for (int i = 0; i < GS_NST; i++) { mbar_init(barFull + 8 * i, 1); mbar_init(barEmpty + 8 * i, 8); }
        mbar_init(barRed, 1);
        fence_mbar_init();
        mbar_expect_tx(barRed, 32768);
    }
    __syncthreads();
    cluster_sync_all();
    if (warp == 8) {
        if (lane == 0) {
            {
                uint32_t n = 0;
                while (ld_acquire_u32(p.tile_flags + mt) < p.tile_target) { if (++n > (1u << 24)) break; __nanosleep(200); }
                fence_proxy_async_all();
            }
            for (int i = 0; i < p.kblocks_half; i++) {
                int slot = i % GS_NST;
                if (i >= GS_NST) mbar_wait(barEmpty + 8 * slot, ((i / GS_NST) - 1) & 1);
                mbar_expect_tx(barFull + 8 * slot, 32768);
                int kb = kh * p.kblocks_half + i;
                tma_load_3d(sS + slot * 32768, &p.tmA, 0, mt * 128, kb, barFull + 8 * slot);
                tma_load_3d(sS + slot * 32768 + 16384, &p.tmB, 0, kb * 64, nt * 2, barFull + 8 * slot);
            }
        }
    } else {
        const int wg = warp >> 2, wq = warp & 3;
        float acc[64];
        int prev = 0;
        for (int i = 0; i < p.kblocks_half; i++) {
            int slot = i % GS_NST;
            mbar_wait(barFull + 8 * slot, (i / GS_NST) & 1);
            wg_fence();
            uint64_t da = make_desc(sS + slot * 32768 + wg * 8192, 16, 1024);
            uint64_t db = make_desc(sS + slot * 32768 + 16384, 8192, 1024);
#pragma unroll
            for (int kk = 0; kk < 4; kk++)
                wgmma_m64n128k16_ss_tb(acc, da + (uint64_t)(kk * 2), db + (uint64_t)(kk * 128), (i | kk) != 0);
            wg_commit();
            if (i > 0) { wg_wait<1>(); if (lane == 0) mbar_arrive(barEmpty + 8 * prev); }
            prev = slot;
        }
        wg_wait<0>();
        const uint32_t peer = kh ^ 1;
        const uint32_t rbuf = mapa_u32(sR, peer), rbar = mapa_u32(barRed, peer);
        const int tw = threadIdx.x;
#pragma unroll
        for (int j = 0; j < 8; j++) {
            float a[4];
#pragma unroll
            for (int i = 0; i < 4; i++) a[i] = kh == 0 ? acc[(8 + j) * 4 + i] : acc[j * 4 + i];
            st_async_v4(rbuf + (j * 256 + tw) * 16, __float_as_uint(a[0]), __float_as_uint(a[1]), __float_as_uint(a[2]), __float_as_uint(a[3]), rbar);
        }
        mbar_wait(barRed, 0);
        named_bar_sync(1, 256);
        const uint32_t stage = sS + wg * 8192;
        const int mrow = wq * 16 + (lane & 7) + ((lane >> 3) & 1) * 8, mcolh = lane >> 4;
#pragma unroll
        for (int c = 0; c < 4; c++) {
            uint32_t r[4];
#pragma unroll
            for (int e = 0; e < 2; e++) {
                int j = c * 2 + e;
                float4 v;
                asm volatile("ld.shared.v4.f32 {%0,%1,%2,%3}, [%4];" : "=f"(v.x), "=f"(v.y), "=f"(v.z), "=f"(v.w) : "r"(sR + (j * 256 + tw) * 16) : "memory");
                float a[4];
#pragma unroll
                for (int i = 0; i < 4; i++) a[i] = kh == 0 ? acc[j * 4 + i] : acc[(8 + j) * 4 + i];
                r[e * 2 + 0] = pack_bf16(a[0] + v.x, a[1] + v.y);
                r[e * 2 + 1] = pack_bf16(a[2] + v.z, a[3] + v.w);
            }
            int chunk = (c * 2 + mcolh) ^ (mrow & 7);
            stmatrix_x4(stage + mrow * 128 + chunk * 16, r[0], r[1], r[2], r[3]);
        }
        fence_proxy_async_smem();
        named_bar_sync(2 + wg, 128);
        if ((threadIdx.x & 127) == 0) {
            tma_store_3d(&p.tmC, stage, 0, mt * 128 + wg * 64, p.c_col64 + nt * 2 + kh);
            bulk_commit();
            bulk_wait_read0();
        }
    }
    __syncthreads();
    cluster_sync_all();
}

typedef CUresult (*PFN_encodeTiled)(CUtensorMap*, CUtensorMapDataType, cuuint32_t, void*, const cuuint64_t*, const cuuint64_t*,
                                    const cuuint32_t*, const cuuint32_t*, CUtensorMapInterleave, CUtensorMapSwizzle,
                                    CUtensorMapL2promotion, CUtensorMapFloatOOBfill);
static PFN_encodeTiled g_encode = nullptr;
static void init_encode() {
    if (g_encode) return;
    void* fn = nullptr;
    cudaDriverEntryPointQueryResult st;
    cudaGetDriverEntryPoint("cuTensorMapEncodeTiled", &fn, cudaEnableDefault, &st);
    g_encode = (PFN_encodeTiled)fn;
}
static CUtensorMap make_tmap_3d64(const void* ptr, uint64_t rows, uint64_t cols, uint64_t ld, uint32_t box_rows, uint32_t box_c64) {
    CUtensorMap tm;
    cuuint64_t dims[3] = {64, rows, cols / 64};
    cuuint64_t strides[2] = {ld * 2, 128};
    cuuint32_t box[3] = {64, box_rows, box_c64};
    cuuint32_t es[3] = {1, 1, 1};
    g_encode(&tm, CU_TENSOR_MAP_DATA_TYPE_BFLOAT16, 3, (void*)ptr, dims, strides, box, es, CU_TENSOR_MAP_INTERLEAVE_NONE,
             CU_TENSOR_MAP_SWIZZLE_128B, CU_TENSOR_MAP_L2_PROMOTION_L2_128B, CU_TENSOR_MAP_FLOAT_OOB_FILL_NONE);
    return tm;
}

__device__ __align__(1024) bf16 g_qkvA[2048 * 1536];
__device__ __align__(1024) bf16 g_oA[2048 * 512];
__device__ __align__(1024) bf16 g_qkvB[2048 * 12288];
__device__ __align__(1024) bf16 g_kvmem[64 * 8 * 8192];
__device__ __align__(1024) bf16 g_oB[2048 * 4096];
__device__ __align__(1024) float g_part[2 * 64 * 256];
__device__ __align__(128) unsigned int g_flags[192];

__global__ void cleanup_kernel() {
    const int i = blockIdx.x * blockDim.x + threadIdx.x;
    const int n = gridDim.x * blockDim.x;
    uint4 z = make_uint4(0, 0, 0, 0);
    for (int k = i; k < 2 * 64 * 64; k += n) reinterpret_cast<uint4*>(g_part)[k] = z;
    if (i < 192) g_flags[i] = 0u;
}

__global__ void delay_kernel() {}

template <typename T> static T* sym_addr(T& sym) { void* p = nullptr; cudaGetSymbolAddress(&p, sym); return (T*)p; }

extern "C" void kernel_launch(void* const* d_in, const int* in_sizes, int n_in, void* d_out, int out_size) {
    const bf16* A_x = (const bf16*)d_in[0];
    const bf16* A_wqkv = (const bf16*)d_in[1];
    const bf16* A_wo = (const bf16*)d_in[2];
    const bf16* B_x = (const bf16*)d_in[3];
    const bf16* B_mem0 = (const bf16*)d_in[4];
    const bf16* B_Wq = (const bf16*)d_in[5];
    const bf16* B_Wk = (const bf16*)d_in[6];
    const bf16* B_Wv = (const bf16*)d_in[7];
    const bf16* B_Wo = (const bf16*)d_in[8];
    bf16* out = (bf16*)d_out;

    static bool inited = false;
    static cudaStream_t s1, s2;
    static cudaEvent_t e_kv, e_s1, e_ch;
    if (!inited) {
        init_encode();
        cudaFuncSetAttribute(gemm_w_kernel, cudaFuncAttributeMaxDynamicSharedMemorySize, GW_SMEM);
        cudaFuncSetAttribute(gemm_s_kernel, cudaFuncAttributeMaxDynamicSharedMemorySize, GS_SMEM);
        cudaFuncSetAttribute(chain_kernel, cudaFuncAttributeMaxDynamicSharedMemorySize, CH_SMEM);
        cudaFuncSetAttribute(chain_kernel, cudaFuncAttributeNonPortableClusterSizeAllowed, 1);
        cudaFuncSetAttribute(attn_a_kernel, cudaFuncAttributeMaxDynamicSharedMemorySize, AA_SMEM);
        cudaFuncSetAttribute(attn_b_kernel, cudaFuncAttributeMaxDynamicSharedMemorySize, AB_SMEM);
        int plo = 0, phi = 0;
        cudaDeviceGetStreamPriorityRange(&plo, &phi);
        cudaStreamCreateWithPriority(&s1, cudaStreamNonBlocking, plo);
        cudaStreamCreateWithPriority(&s2, cudaStreamNonBlocking, phi);
        cudaEventCreateWithFlags(&e_kv, cudaEventDisableTiming);
        cudaEventCreateWithFlags(&e_s1, cudaEventDisableTiming);
        cudaEventCreateWithFlags(&e_ch, cudaEventDisableTiming);
        inited = true;
    }
    void *qkvA, *oA, *qkvB, *kvmem, *oB, *part, *membuf, *flags;
    cudaGetSymbolAddress(&qkvA, g_qkvA); cudaGetSymbolAddress(&oA, g_oA); cudaGetSymbolAddress(&qkvB, g_qkvB);
    cudaGetSymbolAddress(&kvmem, g_kvmem); cudaGetSymbolAddress(&oB, g_oB); cudaGetSymbolAddress(&part, g_part);
    membuf = nullptr; cudaGetSymbolAddress(&flags, g_flags);
    cudaStream_t s0 = cudaStreamPerThread;

    cudaEventRecord(e_kv, s0);
    cudaStreamWaitEvent(s1, e_kv, 0);
    cudaStreamWaitEvent(s2, e_kv, 0);
    ChainParams pc;
    pc.tmW[0] = make_tmap_3d64(B_Wq, 512, 4096, 4096, 256, 1);
    pc.tmW[1] = make_tmap_3d64(B_Wk, 512, 4096, 4096, 256, 1);
    pc.tmW[2] = make_tmap_3d64(B_Wv, 512, 4096, 4096, 256, 1);
    pc.tmWo = make_tmap_3d64(B_Wo, 4096, 512, 512, 128, 1);
    pc.tmKV = make_tmap_3d64(qkvB, 2048, 12288, 12288, 32, 1);
    pc.mem0 = B_mem0; pc.kvmem = (bf16*)kvmem; pc.part = (float*)part; pc.membuf = (uint4*)membuf;
    pc.flags = (const unsigned int*)flags; pc.flag_target = 128; pc.dbg = nullptr; pc.seg_flags = (unsigned int*)flags + 64;
    {
        cudaLaunchConfig_t cfg = {};
        cfg.gridDim = dim3(64); cfg.blockDim = dim3(384); cfg.dynamicSmemBytes = CH_SMEM; cfg.stream = s2;
        cudaLaunchAttribute at[2];
        at[0].id = cudaLaunchAttributeClusterDimension; at[0].val.clusterDim.x = 16; at[0].val.clusterDim.y = 1; at[0].val.clusterDim.z = 1;
        cfg.attrs = at; cfg.numAttrs = 1;
        cudaLaunchKernelEx(&cfg, chain_kernel, pc);
    }

    cudaEventRecord(e_ch, s2);
    delay_kernel<<<1, 32, 0, s1>>>();
    GemmWParams pkv;
    pkv.tmA = make_tmap_3d64(B_x, 2048, 512, 512, 128, 1);
    pkv.tmB[0] = make_tmap_3d64(B_Wk, 512, 4096, 4096, 64, 2);
    pkv.tmB[1] = make_tmap_3d64(B_Wv, 512, 4096, 4096, 64, 2);
    pkv.tmB[2] = make_tmap_3d64(B_Wq, 512, 4096, 4096, 64, 2);
    pkv.tmC = make_tmap_3d64(qkvB, 2048, 12288, 12288, 128, 1);
    pkv.ntiles_per_mat = 32; pkv.c_col64[0] = 64; pkv.c_col64[1] = 128; pkv.c_col64[2] = 0;
    pkv.m_splits = 1; pkv.mtiles_per_cta = 16; pkv.flag_mats = 2; pkv.flags = (unsigned int*)flags;
    gemm_w_kernel<<<64, 384, GW_SMEM, s1>>>(pkv);

    GemmWParams pq = pkv;
    pq.tmB[0] = pkv.tmB[2]; pq.c_col64[0] = 0; pq.m_splits = 2; pq.mtiles_per_cta = 8; pq.flag_mats = 0; pq.flags = nullptr;
    gemm_w_kernel<<<64, 384, GW_SMEM, s1>>>(pq);

    GemmWParams p1;
    p1.tmA = make_tmap_3d64(A_x, 2048, 512, 512, 128, 1);
    p1.tmB[0] = make_tmap_3d64(A_wqkv, 512, 1536, 1536, 64, 2); p1.tmB[1] = p1.tmB[0]; p1.tmB[2] = p1.tmB[0];
    p1.tmC = make_tmap_3d64(qkvA, 2048, 1536, 1536, 128, 1);
    p1.ntiles_per_mat = 12; p1.c_col64[0] = p1.c_col64[1] = p1.c_col64[2] = 0;
    p1.m_splits = 4; p1.mtiles_per_cta = 4; p1.flag_mats = 0; p1.flags = nullptr;
    gemm_w_kernel<<<48, 384, GW_SMEM, s1>>>(p1);

    AttnAParams pa;
    {
        cuuint64_t dims[2] = {1536, 2048}; cuuint64_t strides[1] = {3072}; cuuint32_t box[2] = {16, AA_KT}; cuuint32_t es[2] = {1, 1};
        g_encode(&pa.tmKV, CU_TENSOR_MAP_DATA_TYPE_BFLOAT16, 2, qkvA, dims, strides, box, es, CU_TENSOR_MAP_INTERLEAVE_NONE,
                 CU_TENSOR_MAP_SWIZZLE_32B, CU_TENSOR_MAP_L2_PROMOTION_L2_128B, CU_TENSOR_MAP_FLOAT_OOB_FILL_NONE);
    }
    pa.qkv = (const bf16*)qkvA; pa.o = (bf16*)oA;
    attn_a_kernel<<<256, 256, AA_SMEM, s1>>>(pa);

    GemmWParams p2;
    p2.tmA = make_tmap_3d64(oA, 2048, 512, 512, 128, 1);
    p2.tmB[0] = make_tmap_3d64(A_wo, 512, 512, 512, 64, 2); p2.tmB[1] = p2.tmB[0]; p2.tmB[2] = p2.tmB[0];
    p2.tmC = make_tmap_3d64(out, 2048, 1024, 1024, 128, 1);
    p2.ntiles_per_mat = 4; p2.c_col64[0] = p2.c_col64[1] = p2.c_col64[2] = 0;
    p2.m_splits = 16; p2.mtiles_per_cta = 1; p2.flag_mats = 0; p2.flags = nullptr;
    gemm_w_kernel<<<64, 384, GW_SMEM, s1>>>(p2);

    AttnBParams pb;
    pb.tmQKV = make_tmap_3d64(qkvB, 2048, 12288, 12288, 32, 1);
    pb.tmKVM = make_tmap_3d64(kvmem, 512, 8192, 8192, 8, 1);
    pb.tmO = make_tmap_3d64(oB, 2048, 4096, 4096, 32, 1);
    pb.seg_flags = (const unsigned int*)flags + 64; pb.seg_target = 256; pb.tile_flags = (unsigned int*)flags + 128;
    attn_b_kernel<<<512, 128, AB_SMEM, s1>>>(pb);

    GemmSParams p4;
    p4.tmA = make_tmap_3d64(oB, 2048, 4096, 4096, 128, 1);
    p4.tmB = make_tmap_3d64(B_Wo, 4096, 512, 512, 64, 2);
    p4.tmC = make_tmap_3d64(out, 2048, 1024, 1024, 64, 1);
    p4.n_tiles = 4; p4.kblocks_half = 32; p4.c_col64 = 8;
    p4.tile_flags = (const unsigned int*)flags + 128; p4.tile_target = 128;
    {
        cudaLaunchConfig_t cfg = {};
        cfg.gridDim = dim3(128); cfg.blockDim = dim3(288); cfg.dynamicSmemBytes = GS_SMEM; cfg.stream = s1;
        cudaLaunchAttribute at[2];
        at[0].id = cudaLaunchAttributeClusterDimension; at[0].val.clusterDim.x = 2; at[0].val.clusterDim.y = 1; at[0].val.clusterDim.z = 1;
        at[1].id = cudaLaunchAttributeProgrammaticStreamSerialization; at[1].val.programmaticStreamSerializationAllowed = 1;
        cfg.attrs = at; cfg.numAttrs = 2;
        cudaLaunchKernelEx(&cfg, gemm_s_kernel, p4);
    }
    cudaEventRecord(e_s1, s1);
    cudaStreamWaitEvent(s0, e_s1, 0);
    cudaStreamWaitEvent(s0, e_ch, 0);
    cleanup_kernel<<<64, 256, 0, s0>>>();
}
```

```cpp
#include <cuda_runtime.h>
#include <cuda_bf16.h>
#include <cuda.h>
#include <stdint.h>

typedef __nv_bfloat16 bf16;

__device__ __forceinline__ uint32_t smem_u32(const void* p) { return (uint32_t)__cvta_generic_to_shared(p); }
__device__ __forceinline__ void mbar_init(uint32_t bar, uint32_t cnt) {
    asm volatile("mbarrier.init.shared::cta.b64 [%0], %1;" :: "r"(bar), "r"(cnt) : "memory");
}
__device__ __forceinline__ void mbar_expect_tx(uint32_t bar, uint32_t bytes) {
    asm volatile("mbarrier.arrive.expect_tx.shared::cta.b64 _, [%0], %1;" :: "r"(bar), "r"(bytes) : "memory");
}
__device__ __forceinline__ void mbar_arrive(uint32_t bar) {
    asm volatile("mbarrier.arrive.shared::cta.b64 _, [%0];" :: "r"(bar) : "memory");
}
__device__ __forceinline__ bool mbar_try_wait(uint32_t bar, uint32_t parity) {
    uint32_t ok;
    asm volatile("{\n.reg .pred p;\nmbarrier.try_wait.parity.shared::cta.b64 p, [%1], %2;\nselp.u32 %0, 1, 0, p;\n}"
                 : "=r"(ok) : "r"(bar), "r"(parity) : "memory");
    return ok != 0;
}
__device__ __forceinline__ void mbar_wait(uint32_t bar, uint32_t parity) {
    uint32_t n = 0;
    while (!mbar_try_wait(bar, parity)) { if (++n > (1u << 20)) break; }
}
__device__ __forceinline__ void fence_proxy_async_smem() { asm volatile("fence.proxy.async.shared::cta;" ::: "memory"); }
__device__ __forceinline__ void fence_proxy_async_all() { asm volatile("fence.proxy.async;" ::: "memory"); }
__device__ __forceinline__ void fence_mbar_init() { asm volatile("fence.mbarrier_init.release.cluster;" ::: "memory"); }

__device__ __forceinline__ void tma_load_3d(uint32_t dst, const CUtensorMap* tm, int c0, int c1, int c2, uint32_t bar) {
    asm volatile("cp.async.bulk.tensor.3d.shared::cluster.global.mbarrier::complete_tx::bytes [%0], [%1, {%3, %4, %5}], [%2];"
                 :: "r"(dst), "l"(tm), "r"(bar), "r"(c0), "r"(c1), "r"(c2) : "memory");
}
__device__ __forceinline__ void tma_load_2d(uint32_t dst, const CUtensorMap* tm, int c0, int c1, uint32_t bar) {
    asm volatile("cp.async.bulk.tensor.2d.shared::cluster.global.mbarrier::complete_tx::bytes [%0], [%1, {%3, %4}], [%2];"
                 :: "r"(dst), "l"(tm), "r"(bar), "r"(c0), "r"(c1) : "memory");
}
__device__ __forceinline__ void tma_store_3d(const CUtensorMap* tm, uint32_t src, int c0, int c1, int c2) {
    asm volatile("cp.async.bulk.tensor.3d.global.shared::cta.bulk_group [%0, {%2, %3, %4}], [%1];"
                 :: "l"(tm), "r"(src), "r"(c0), "r"(c1), "r"(c2) : "memory");
}
__device__ __forceinline__ void bulk_commit() { asm volatile("cp.async.bulk.commit_group;" ::: "memory"); }
__device__ __forceinline__ void bulk_wait_read0() { asm volatile("cp.async.bulk.wait_group.read 0;" ::: "memory"); }
__device__ __forceinline__ void bulk_wait_all0() { asm volatile("cp.async.bulk.wait_group 0;" ::: "memory"); }
__device__ __forceinline__ void prefetch_tmap(const CUtensorMap* tm) {
    asm volatile("prefetch.tensormap [%0];" :: "l"(tm) : "memory");
}

__device__ __forceinline__ void wg_fence() { asm volatile("wgmma.fence.sync.aligned;" ::: "memory"); }
__device__ __forceinline__ void wg_commit() { asm volatile("wgmma.commit_group.sync.aligned;" ::: "memory"); }
template <int N> __device__ __forceinline__ void wg_wait() { asm volatile("wgmma.wait_group.sync.aligned %0;" :: "n"(N) : "memory"); }

__device__ __forceinline__ void named_bar_sync(int id, int nthreads) {
    asm volatile("bar.sync %0, %1;" :: "r"(id), "r"(nthreads) : "memory");
}
__device__ __forceinline__ void named_bar_arrive(int id, int nthreads) {
    asm volatile("bar.arrive %0, %1;" :: "r"(id), "r"(nthreads) : "memory");
}

__device__ __forceinline__ uint64_t make_desc(uint32_t saddr, uint32_t lbo_bytes, uint32_t sbo_bytes) {
    return (uint64_t)((saddr & 0x3FFFF) >> 4) | ((uint64_t)(lbo_bytes >> 4) << 16) | ((uint64_t)(sbo_bytes >> 4) << 32) | ((uint64_t)1 << 62);
}

__device__ __forceinline__ uint32_t pack_bf16(float lo, float hi) {
    uint32_t r;
    asm("cvt.rn.bf16x2.f32 %0, %1, %2;" : "=r"(r) : "f"(hi), "f"(lo));
    return r;
}
__device__ __forceinline__ void stmatrix_x4(uint32_t addr, uint32_t r0, uint32_t r1, uint32_t r2, uint32_t r3) {
    asm volatile("stmatrix.sync.aligned.m8n8.x4.shared.b16 [%0], {%1,%2,%3,%4};" :: "r"(addr), "r"(r0), "r"(r1), "r"(r2), "r"(r3) : "memory");
}
__device__ __forceinline__ void ldmatrix_x4(uint32_t& r0, uint32_t& r1, uint32_t& r2, uint32_t& r3, uint32_t addr) {
    asm volatile("ldmatrix.sync.aligned.m8n8.x4.shared.b16 {%0,%1,%2,%3}, [%4];" : "=r"(r0), "=r"(r1), "=r"(r2), "=r"(r3) : "r"(addr) : "memory");
}
__device__ __forceinline__ void ldmatrix_x4_t(uint32_t& r0, uint32_t& r1, uint32_t& r2, uint32_t& r3, uint32_t addr) {
    asm volatile("ldmatrix.sync.aligned.m8n8.x4.trans.shared.b16 {%0,%1,%2,%3}, [%4];" : "=r"(r0), "=r"(r1), "=r"(r2), "=r"(r3) : "r"(addr) : "memory");
}
__device__ __forceinline__ void ldmatrix_x2(uint32_t& r0, uint32_t& r1, uint32_t addr) {
    asm volatile("ldmatrix.sync.aligned.m8n8.x2.shared.b16 {%0,%1}, [%2];" : "=r"(r0), "=r"(r1) : "r"(addr) : "memory");
}
__device__ __forceinline__ void ldmatrix_x2_t(uint32_t& r0, uint32_t& r1, uint32_t addr) {
    asm volatile("ldmatrix.sync.aligned.m8n8.x2.trans.shared.b16 {%0,%1}, [%2];" : "=r"(r0), "=r"(r1) : "r"(addr) : "memory");
}
__device__ __forceinline__ void mma16816(float* c, const uint32_t* a, uint32_t b0, uint32_t b1) {
    asm volatile("mma.sync.aligned.m16n8k16.row.col.f32.bf16.bf16.f32 {%0,%1,%2,%3}, {%4,%5,%6,%7}, {%8,%9}, {%0,%1,%2,%3};"
                 : "+f"(c[0]), "+f"(c[1]), "+f"(c[2]), "+f"(c[3]) : "r"(a[0]), "r"(a[1]), "r"(a[2]), "r"(a[3]), "r"(b0), "r"(b1));
}

__device__ __forceinline__ void wgmma_m64n128k16_ss_tb(float* d, uint64_t da, uint64_t db, int scale_d) {
    asm volatile(
        "{\n.reg .pred p;\nsetp.ne.b32 p, %66, 0;\n"
        "wgmma.mma_async.sync.aligned.m64n128k16.f32.bf16.bf16 "
        "{%0,%1,%2,%3,%4,%5,%6,%7,%8,%9,%10,%11,%12,%13,%14,%15,"
        "%16,%17,%18,%19,%20,%21,%22,%23,%24,%25,%26,%27,%28,%29,%30,%31,"
        "%32,%33,%34,%35,%36,%37,%38,%39,%40,%41,%42,%43,%44,%45,%46,%47,"
        "%48,%49,%50,%51,%52,%53,%54,%55,%56,%57,%58,%59,%60,%61,%62,%63},"
        " %64, %65, p, 1, 1, 0, 1;\n}\n"
        : "+f"(d[0]), "+f"(d[1]), "+f"(d[2]), "+f"(d[3]), "+f"(d[4]), "+f"(d[5]), "+f"(d[6]), "+f"(d[7]),
          "+f"(d[8]), "+f"(d[9]), "+f"(d[10]), "+f"(d[11]), "+f"(d[12]), "+f"(d[13]), "+f"(d[14]), "+f"(d[15]),
          "+f"(d[16]), "+f"(d[17]), "+f"(d[18]), "+f"(d[19]), "+f"(d[20]), "+f"(d[21]), "+f"(d[22]), "+f"(d[23]),
          "+f"(d[24]), "+f"(d[25]), "+f"(d[26]), "+f"(d[27]), "+f"(d[28]), "+f"(d[29]), "+f"(d[30]), "+f"(d[31]),
          "+f"(d[32]), "+f"(d[33]), "+f"(d[34]), "+f"(d[35]), "+f"(d[36]), "+f"(d[37]), "+f"(d[38]), "+f"(d[39]),
          "+f"(d[40]), "+f"(d[41]), "+f"(d[42]), "+f"(d[43]), "+f"(d[44]), "+f"(d[45]), "+f"(d[46]), "+f"(d[47]),
          "+f"(d[48]), "+f"(d[49]), "+f"(d[50]), "+f"(d[51]), "+f"(d[52]), "+f"(d[53]), "+f"(d[54]), "+f"(d[55]),
          "+f"(d[56]), "+f"(d[57]), "+f"(d[58]), "+f"(d[59]), "+f"(d[60]), "+f"(d[61]), "+f"(d[62]), "+f"(d[63])
        : "l"(da), "l"(db), "r"(scale_d));
}

__device__ __forceinline__ void wgmma_m64n128k16_rs(float* d, const uint32_t* a, uint64_t db, int scale_d) {
    asm volatile(
        "{\n.reg .pred p;\nsetp.ne.b32 p, %69, 0;\n"
        "wgmma.mma_async.sync.aligned.m64n128k16.f32.bf16.bf16 "
        "{%0,%1,%2,%3,%4,%5,%6,%7,%8,%9,%10,%11,%12,%13,%14,%15,"
        "%16,%17,%18,%19,%20,%21,%22,%23,%24,%25,%26,%27,%28,%29,%30,%31,"
        "%32,%33,%34,%35,%36,%37,%38,%39,%40,%41,%42,%43,%44,%45,%46,%47,"
        "%48,%49,%50,%51,%52,%53,%54,%55,%56,%57,%58,%59,%60,%61,%62,%63},"
        " {%64,%65,%66,%67}, %68, p, 1, 1, 0;\n}\n"
        : "+f"(d[0]), "+f"(d[1]), "+f"(d[2]), "+f"(d[3]), "+f"(d[4]), "+f"(d[5]), "+f"(d[6]), "+f"(d[7]),
          "+f"(d[8]), "+f"(d[9]), "+f"(d[10]), "+f"(d[11]), "+f"(d[12]), "+f"(d[13]), "+f"(d[14]), "+f"(d[15]),
          "+f"(d[16]), "+f"(d[17]), "+f"(d[18]), "+f"(d[19]), "+f"(d[20]), "+f"(d[21]), "+f"(d[22]), "+f"(d[23]),
          "+f"(d[24]), "+f"(d[25]), "+f"(d[26]), "+f"(d[27]), "+f"(d[28]), "+f"(d[29]), "+f"(d[30]), "+f"(d[31]),
          "+f"(d[32]), "+f"(d[33]), "+f"(d[34]), "+f"(d[35]), "+f"(d[36]), "+f"(d[37]), "+f"(d[38]), "+f"(d[39]),
          "+f"(d[40]), "+f"(d[41]), "+f"(d[42]), "+f"(d[43]), "+f"(d[44]), "+f"(d[45]), "+f"(d[46]), "+f"(d[47]),
          "+f"(d[48]), "+f"(d[49]), "+f"(d[50]), "+f"(d[51]), "+f"(d[52]), "+f"(d[53]), "+f"(d[54]), "+f"(d[55]),
          "+f"(d[56]), "+f"(d[57]), "+f"(d[58]), "+f"(d[59]), "+f"(d[60]), "+f"(d[61]), "+f"(d[62]), "+f"(d[63])
        : "r"(a[0]), "r"(a[1]), "r"(a[2]), "r"(a[3]), "l"(db), "r"(scale_d));
}
__device__ __forceinline__ void stmatrix_x4_t(uint32_t addr, uint32_t r0, uint32_t r1, uint32_t r2, uint32_t r3) {
    asm volatile("stmatrix.sync.aligned.m8n8.x4.trans.shared.b16 [%0], {%1,%2,%3,%4};" :: "r"(addr), "r"(r0), "r"(r1), "r"(r2), "r"(r3) : "memory");
}
template <int R> __device__ __forceinline__ void reg_alloc() { asm volatile("setmaxnreg.inc.sync.aligned.u32 %0;" :: "n"(R)); }
template <int R> __device__ __forceinline__ void reg_dealloc() { asm volatile("setmaxnreg.dec.sync.aligned.u32 %0;" :: "n"(R)); }

#define TL_START(k)
#define TL_END(k)
struct GemmWParams {
    CUtensorMap tmA;
    CUtensorMap tmB[3];
    CUtensorMap tmC;
    int ntiles_per_mat;
    int c_col64[3];
    int m_splits;
    int mtiles_per_cta;
    int flag_mats;
    unsigned int* flags;
    int tl_id;
};

constexpr int GW_NST = 11;
constexpr int GW_SMEM = GW_NST * 16384 + 32768 + 256;

__global__ void __launch_bounds__(384, 1) gemm_w_kernel(const __grid_constant__ GemmWParams p) {
    extern __shared__ __align__(1024) unsigned char smem[];
    const uint32_t sA = smem_u32(smem);
    const uint32_t sOut = sA + GW_NST * 16384;
    const uint32_t bars = sOut + 32768;
    const uint32_t barFull = bars, barEmpty = bars + 8 * GW_NST, barStF = bars + 16 * GW_NST, barStE = barStF + 16;
    const int warp = __shfl_sync(0xffffffff, threadIdx.x >> 5, 0), lane = threadIdx.x & 31;
    TL_START(p.tl_id);
    const int gnt = blockIdx.x / p.m_splits;
    const int ms = blockIdx.x % p.m_splits;
    const int mat = gnt / p.ntiles_per_mat;
    const int nt = gnt % p.ntiles_per_mat;
    const int tile0 = ms * p.mtiles_per_cta;
    const int ntl = p.mtiles_per_cta;

    if (threadIdx.x == 0) {
        for (int i = 0; i < GW_NST; i++) { mbar_init(barFull + 8 * i, 1); mbar_init(barEmpty + 8 * i, 8); }
        for (int i = 0; i < 2; i++) { mbar_init(barStF + 8 * i, 4); mbar_init(barStE + 8 * i, 1); }
        fence_mbar_init();
    }
    __syncthreads();

    const int wgi = __shfl_sync(0xffffffff, threadIdx.x >> 7, 0);
    if (wgi == 0) {
        reg_dealloc<40>();
        if (warp == 0 && lane == 0) {
            const CUtensorMap* tmB = &p.tmB[mat];
            const int total = 8 + ntl * 8;
            for (int idx = 0; idx < total; idx++) {
                int slot = idx % GW_NST;
                if (idx >= GW_NST) mbar_wait(barEmpty + 8 * slot, ((idx / GW_NST) - 1) & 1);
                mbar_expect_tx(barFull + 8 * slot, 16384);
                if (idx < 8) tma_load_3d(sA + slot * 16384, tmB, 0, idx * 64, nt * 2, barFull + 8 * slot);
                else {
                    int t = (idx - 8) >> 3, j = (idx - 8) & 7;
                    tma_load_3d(sA + slot * 16384, &p.tmA, 0, (tile0 + t) * 128, j, barFull + 8 * slot);
                }
            }
        } else if ((warp == 1 || warp == 2) && lane == 0) {
            const int wg = warp - 1;
            const bool do_flag = (p.flags != nullptr) && (mat < p.flag_mats);
            for (int t = 0; t < ntl; t++) {
                mbar_wait(barStF + 8 * wg, t & 1);
                tma_store_3d(&p.tmC, sOut + wg * 16384, 0, (tile0 + t) * 128, p.c_col64[mat] + nt * 2 + wg);
                bulk_commit();
                bulk_wait_read0();
                mbar_arrive(barStE + 8 * wg);
                if (do_flag) {
                    bulk_wait_all0();
                    fence_proxy_async_all();
                    __threadfence();
                    atomicAdd(p.flags + tile0 + t, 1u);
                }
            }
            bulk_wait_all0();
        }
    } else {
        reg_alloc<232>();
        const int wg = (warp >> 2) - 1, wq = warp & 3;
        uint32_t w[32][4];
        float acc[64];
        {
            const int krow = (lane & 7) + ((lane >> 4) & 1) * 8;
            const int chunk = wq * 2 + ((lane >> 3) & 1);
#pragma unroll
            for (int kb = 0; kb < 8; kb++) {
                mbar_wait(barFull + 8 * kb, 0);
#pragma unroll
                for (int kk = 0; kk < 4; kk++) {
                    int r = kk * 16 + krow;
                    uint32_t addr = sA + kb * 16384 + wg * 8192 + r * 128 + ((chunk ^ (r & 7)) << 4);
                    ldmatrix_x4_t(w[kb * 4 + kk][0], w[kb * 4 + kk][1], w[kb * 4 + kk][2], w[kb * 4 + kk][3], addr);
                }
                __syncwarp();
                if (lane == 0) mbar_arrive(barEmpty + 8 * kb);
            }
        }
        int idx = 8;
        for (int t = 0; t < ntl; t++) {
            int prev_slot = 0;
            if (wg == 0) { if (t > 0) named_bar_sync(3, 256); }
            else named_bar_sync(4, 256);
#pragma unroll
            for (int j = 0; j < 8; j++, idx++) {
                int slot = idx % GW_NST;
                mbar_wait(barFull + 8 * slot, (idx / GW_NST) & 1);
                wg_fence();
                uint64_t db = make_desc(sA + slot * 16384, 16, 1024);
#pragma unroll
                for (int kk = 0; kk < 4; kk++)
                    wgmma_m64n128k16_rs(acc, w[j * 4 + kk], db + (uint64_t)(kk * 2), (j | kk) != 0);
                wg_commit();
                if (j == 7) {
                    if (wg == 0) named_bar_arrive(4, 256);
                    else if (t + 1 < ntl) named_bar_arrive(3, 256);
                }
                if (j > 0) {
                    wg_wait<1>();
                    if (lane == 0) mbar_arrive(barEmpty + 8 * prev_slot);
                }
                prev_slot = slot;
            }
            wg_wait<0>();
            if (lane == 0) mbar_arrive(barEmpty + 8 * prev_slot);
            if (t > 0) mbar_wait(barStE + 8 * wg, (t - 1) & 1);
            const uint32_t sbase = sOut + wg * 16384;
            const int mid = lane >> 3;
            const int chunk = wq * 2 + (mid & 1);
#pragma unroll
            for (int nb = 0; nb < 8; nb++) {
                const int a0 = nb * 8;
                uint32_t r0 = pack_bf16(acc[a0 + 0], acc[a0 + 1]);
                uint32_t r1 = pack_bf16(acc[a0 + 2], acc[a0 + 3]);
                uint32_t r2 = pack_bf16(acc[a0 + 4], acc[a0 + 5]);
                uint32_t r3 = pack_bf16(acc[a0 + 6], acc[a0 + 7]);
                int tok = nb * 16 + (mid >> 1) * 8 + (lane & 7);
                stmatrix_x4_t(sbase + tok * 128 + ((chunk ^ (tok & 7)) << 4), r0, r1, r2, r3);
            }
            fence_proxy_async_smem();
            __syncwarp();
            if (lane == 0) mbar_arrive(barStF + 8 * wg);
        }
    }
}

#define PACE 0
#define NSTEPS 64
#define POLL_B 1
#define POLL_R 1
struct ChainParams {
    CUtensorMap tmW[3];
    CUtensorMap tmWo;
    CUtensorMap tmKV;
    const bf16* mem0;
    bf16* kvmem;
    float* part;
    uint4* membuf;
    const unsigned int* flags;
    unsigned int flag_target;
    unsigned int* seg_flags;
    long long* dbg;
};

constexpr int CH_MEM_STRIDE = 1040;
constexpr int CH_Q_STRIDE = 144;
constexpr int CH_O_STRIDE = 272;
constexpr int CH_NKV = 4;
constexpr int CH_KV_BYTES = 15360;
constexpr int CH_OFF_WO = 0;
constexpr int CH_OFF_WV = 65536;
constexpr int CH_OFF_KV = 131072;
constexpr int CH_OFF_MEM = CH_OFF_KV + CH_NKV * CH_KV_BYTES;
constexpr int CH_OFF_RS = CH_OFF_MEM + 8192;
constexpr int CH_OFF_STG = CH_OFF_RS + 8192;
constexpr int CH_OFF_Q = CH_OFF_STG + 512;
constexpr int CH_OFF_O = CH_OFF_Q + 1152;
constexpr int CH_OFF_RED1 = CH_OFF_O + 2176;
constexpr int CH_OFF_SC = CH_OFF_RED1 + 6144;
constexpr int CH_OFF_RED2 = CH_OFF_SC + 1280;
constexpr int CH_OFF_ZERO = CH_OFF_RED2 + 2048;
constexpr int CH_OFF_BAR = CH_OFF_ZERO + 128;
constexpr int CH_OFF_TS = CH_OFF_BAR + 256;
constexpr int CH_SMEM = CH_OFF_TS + 1024;

__device__ __forceinline__ uint32_t mapa_u32(uint32_t addr, uint32_t rank) {
    uint32_t r; asm volatile("mapa.shared::cluster.u32 %0, %1, %2;" : "=r"(r) : "r"(addr), "r"(rank)); return r;
}
__device__ __forceinline__ void st_async_v4(uint32_t addr, uint32_t a, uint32_t b, uint32_t c, uint32_t d, uint32_t mbar) {
    asm volatile("st.async.shared::cluster.mbarrier::complete_tx::bytes.v4.b32 [%0], {%1,%2,%3,%4}, [%5];"
                 :: "r"(addr), "r"(a), "r"(b), "r"(c), "r"(d), "r"(mbar) : "memory");
}
__device__ __forceinline__ void st_async_v2(uint32_t addr, uint32_t a, uint32_t b, uint32_t mbar) {
    asm volatile("st.async.shared::cluster.mbarrier::complete_tx::bytes.v2.b32 [%0], {%1,%2}, [%3];"
                 :: "r"(addr), "r"(a), "r"(b), "r"(mbar) : "memory");
}
__device__ __forceinline__ bool mbar_try_wait_cl(uint32_t bar, uint32_t parity) {
    uint32_t ok;
    asm volatile("{\n.reg .pred p;\nmbarrier.try_wait.parity.acquire.cluster.shared::cta.b64 p, [%1], %2;\nselp.u32 %0, 1, 0, p;\n}"
                 : "=r"(ok) : "r"(bar), "r"(parity) : "memory");
    return ok != 0;
}
__device__ __forceinline__ void mbar_wait_cl(uint32_t bar, uint32_t parity) {
    uint32_t n = 0;
    while (!mbar_try_wait_cl(bar, parity)) { if (++n > (1u << 20)) break; }
}
__device__ __forceinline__ void cluster_sync_all() {
    asm volatile("barrier.cluster.arrive.aligned;\nbarrier.cluster.wait.aligned;" ::: "memory");
}
__device__ __forceinline__ uint4 ld_relaxed_v4(const void* p) {
    uint4 v;
    asm volatile("ld.relaxed.gpu.global.v4.u32 {%0,%1,%2,%3}, [%4];" : "=r"(v.x), "=r"(v.y), "=r"(v.z), "=r"(v.w) : "l"(p) : "memory");
    return v;
}
__device__ __forceinline__ void st_relaxed_v4(void* p, uint32_t a, uint32_t b, uint32_t c, uint32_t d) {
    asm volatile("st.relaxed.gpu.global.v4.u32 [%0], {%1,%2,%3,%4};" :: "l"(p), "r"(a), "r"(b), "r"(c), "r"(d) : "memory");
}
__device__ __forceinline__ unsigned int ld_acquire_u32(const unsigned int* p) {
    unsigned int v;
    asm volatile("ld.acquire.gpu.global.u32 %0, [%1];" : "=r"(v) : "l"(p) : "memory");
    return v;
}
__device__ __forceinline__ void lds128(uint32_t* r, uint32_t addr) {
    asm volatile("ld.shared.v4.u32 {%0,%1,%2,%3}, [%4];" : "=r"(r[0]), "=r"(r[1]), "=r"(r[2]), "=r"(r[3]) : "r"(addr) : "memory");
}
__device__ __forceinline__ float ex2_approx(float x) { float y; asm("ex2.approx.ftz.f32 %0, %1;" : "=f"(y) : "f"(x)); return y; }
__device__ __forceinline__ void mma_nv(float* c, const uint32_t* a, uint32_t b0, uint32_t b1) {
    asm("mma.sync.aligned.m16n8k16.row.col.f32.bf16.bf16.f32 {%0,%1,%2,%3}, {%4,%5,%6,%7}, {%8,%9}, {%0,%1,%2,%3};"
        : "+f"(c[0]), "+f"(c[1]), "+f"(c[2]), "+f"(c[3]) : "r"(a[0]), "r"(a[1]), "r"(a[2]), "r"(a[3]), "r"(b0), "r"(b1));
}

__device__ __forceinline__ void st_relaxed_v2(void* p, uint32_t a, uint32_t b) {
    asm volatile("st.relaxed.gpu.global.v2.u32 [%0], {%1,%2};" :: "l"(p), "r"(a), "r"(b) : "memory");
}

#define TSX(i)
__global__ void __launch_bounds__(384, 1) chain_kernel(const __grid_constant__ ChainParams p) {
    extern __shared__ __align__(1024) unsigned char smem[];
    const uint32_t sb = smem_u32(smem);
    int tid; asm volatile("mov.u32 %0, %%tid.x;" : "=r"(tid));
    int bid; asm volatile("mov.u32 %0, %%ctaid.x;" : "=r"(bid));
    const int lane = tid & 31;
    const int warp = __shfl_sync(0xffffffff, tid >> 5, 0);
    const int wgi = __shfl_sync(0xffffffff, tid >> 7, 0);
    const int rank = bid & 15, cl = bid >> 4;
    const int head = bid >> 1, half = bid & 1;
    TL_START(0);
    const uint32_t barSc = sb + CH_OFF_BAR, barV = barSc + 8, barLd = barSc + 16, barKV = barSc + 24, barMem = barKV + 8 * CH_NKV, barRS = barMem + 8;

    if (tid == 0) {
        mbar_init(barSc, 1); mbar_init(barV, 1); mbar_init(barLd, 1); mbar_init(barMem, 1); mbar_init(barRS, 1);
        for (int i = 0; i < CH_NKV; i++) mbar_init(barKV + 8 * i, 1);
        fence_mbar_init();
        mbar_expect_tx(barSc, 1280);
        mbar_expect_tx(barV, 1024);
        mbar_expect_tx(barMem, 8192);
        mbar_expect_tx(barRS, 4096);
    }
    if (tid < 32) *reinterpret_cast<uint32_t*>(smem + CH_OFF_ZERO + tid * 4) = 0u;
    __syncthreads();
    cluster_sync_all();
    const uint32_t peer = rank ^ 1;
    const int t4 = lane & 3, g8 = lane >> 2;
    const int lr = lane & 7, lm = lane >> 3;

    if (wgi < 2) {
        reg_alloc<208>();
        const int g = warp >> 1, kh = warp & 1;
        uint32_t wqk[2][16][4];
        {
            const int c64 = head * 2 + half;
            const int krow = lr + ((lane >> 4) & 1) * 8;
            const int chunk = g * 2 + (lm & 1);
            if (tid == 0) {
                mbar_expect_tx(barLd, 131072);
                tma_load_3d(sb + CH_OFF_WO, &p.tmW[0], 0, 0, c64, barLd);
                tma_load_3d(sb + CH_OFF_WO + 32768, &p.tmW[0], 0, 256, c64, barLd);
                tma_load_3d(sb + CH_OFF_WV, &p.tmW[1], 0, 0, c64, barLd);
                tma_load_3d(sb + CH_OFF_WV + 32768, &p.tmW[1], 0, 256, c64, barLd);
            }
            mbar_wait(barLd, 0);
#pragma unroll
            for (int m = 0; m < 2; m++)
#pragma unroll
                for (int ks = 0; ks < 16; ks++) {
                    int r = kh * 256 + ks * 16 + krow;
                    uint32_t addr = sb + (m == 0 ? CH_OFF_WO : CH_OFF_WV) + r * 128 + ((chunk ^ (r & 7)) << 4);
                    ldmatrix_x4_t(wqk[m][ks][0], wqk[m][ks][1], wqk[m][ks][2], wqk[m][ks][3], addr);
                }
            named_bar_sync(7, 256);
            if (tid == 0) {
                mbar_expect_tx(barLd, 131072);
                tma_load_3d(sb + CH_OFF_WV, &p.tmW[2], 0, 0, c64, barLd);
                tma_load_3d(sb + CH_OFF_WV + 32768, &p.tmW[2], 0, 256, c64, barLd);
                for (int i = 0; i < 4; i++) tma_load_3d(sb + CH_OFF_WO + i * 16384, &p.tmWo, 0, head * 128, half * 4 + i, barLd);
            }
            mbar_wait(barLd, 1);
            uint32_t f[16][4];
#pragma unroll
            for (int ks = 0; ks < 16; ks++) {
                int r = kh * 256 + ks * 16 + krow;
                ldmatrix_x4_t(f[ks][0], f[ks][1], f[ks][2], f[ks][3], sb + CH_OFF_WV + r * 128 + ((chunk ^ (r & 7)) << 4));
            }
            named_bar_sync(7, 256);
#pragma unroll
            for (int ks = 0; ks < 16; ks++)
                asm volatile("st.shared.v4.u32 [%0], {%1,%2,%3,%4};" :: "r"(sb + CH_OFF_WV + ((warp * 16 + ks) * 32 + lane) * 16), "r"(f[ks][0]), "r"(f[ks][1]), "r"(f[ks][2]), "r"(f[ks][3]) : "memory");
#pragma unroll
            for (int ks = 0; ks < 8; ks++)
#pragma unroll
                for (int mt = 0; mt < 2; mt++) {
                    int r = ks * 16 + krow;
                    int colchunk = warp * 4 + mt * 2 + (lm & 1);
                    ldmatrix_x4_t(f[ks * 2 + mt][0], f[ks * 2 + mt][1], f[ks * 2 + mt][2], f[ks * 2 + mt][3],
                                  sb + CH_OFF_WO + (colchunk >> 3) * 16384 + r * 128 + (((colchunk & 7) ^ (r & 7)) << 4));
                }
            named_bar_sync(7, 256);
#pragma unroll
            for (int i = 0; i < 16; i++)
                asm volatile("st.shared.v4.u32 [%0], {%1,%2,%3,%4};" :: "r"(sb + CH_OFF_WO + ((warp * 16 + i) * 32 + lane) * 16), "r"(f[i][0]), "r"(f[i][1]), "r"(f[i][2]), "r"(f[i][3]) : "memory");
            named_bar_sync(7, 256);
        }
        const uint32_t wvbase = sb + CH_OFF_WV + (warp * 16 * 32 + lane) * 16;
        const uint32_t wobase = sb + CH_OFF_WO + (warp * 16 * 32 + lane) * 16;
        const uint32_t bAddr = sb + CH_OFF_MEM + kh * 4096 + lr * 64 + ((lm ^ ((lr >> 1) & 3)) << 4);
        const uint32_t redMine = sb + CH_OFF_RED1 + warp * 512 + lane * 16, redOther = sb + CH_OFF_RED1 + (warp ^ 1) * 512 + lane * 16;
        const uint32_t redMineV = sb + CH_OFF_RED1 + 4096 + warp * 256 + lane * 8, redOtherV = sb + CH_OFF_RED1 + 4096 + (warp ^ 1) * 256 + lane * 8;
        const uint32_t qDst = sb + CH_OFF_Q + lr * CH_Q_STRIDE + (g * 16 + (lm & 1) * 8) * 2;
        const uint32_t kvOff = lr * 128 + (((g * 2 + (lm & 1)) ^ lr) << 4);
        const uint32_t peerBase = mapa_u32(sb, peer) - sb;
        const uint32_t oAddr = sb + CH_OFF_O + lr * CH_O_STRIDE + lm * 16;
        const uint32_t rsDst = mapa_u32(sb + CH_OFF_RS + (rank >> 1) * 512 + lane * 16, warp * 2 + half);
        const uint32_t rsBar = mapa_u32(barRS, warp * 2 + half);
        float* llW = p.part + ((size_t)(cl * 16 + rank) * 64 + tid) * 4;
        for (int s = 0; s < NSTEPS; s++) {
            const uint32_t sKV = sb + CH_OFF_KV + (s & (CH_NKV - 1)) * CH_KV_BYTES;
            uint32_t wo[16][4], wv[2][2][4];
#pragma unroll
            for (int i = 0; i < 8; i++) lds128(wo[i], wobase + i * 512);
            lds128(wv[0][0], wvbase); lds128(wv[0][1], wvbase + 512);
            TSX(0);
            if (s == 0) {
                for (int i = tid; i < 512; i += 256) {
                    int tok = i & 7, c = i >> 3;
                    uint4 v = *reinterpret_cast<const uint4*>(p.mem0 + tok * 512 + c * 8);
                    *reinterpret_cast<uint4*>(smem + CH_OFF_MEM + (c >> 2) * 512 + tok * 64 + (((c & 3) ^ ((tok >> 1) & 3)) << 4)) = v;
                }
                named_bar_sync(7, 256);
            } else {
                mbar_wait(barMem, (s - 1) & 1);
                if (tid == 0) mbar_expect_tx(barMem, 8192);
            }
            TSX(1);
            {
                float aq[4], ak[4], av[4];
#pragma unroll
                for (int i = 0; i < 4; i++) { aq[i] = ak[i] = av[i] = 0.f; }
                uint32_t b[2][4];
                ldmatrix_x4(b[0][0], b[0][1], b[0][2], b[0][3], bAddr);
#pragma unroll
                for (int kk = 0; kk < 8; kk++) {
                    if (kk + 1 < 8) {
                        ldmatrix_x4(b[(kk + 1) & 1][0], b[(kk + 1) & 1][1], b[(kk + 1) & 1][2], b[(kk + 1) & 1][3], bAddr + (kk + 1) * 512);
                        lds128(wv[(kk + 1) & 1][0], wvbase + (2 * kk + 2) * 512);
                        lds128(wv[(kk + 1) & 1][1], wvbase + (2 * kk + 3) * 512);
                    }
                    mma_nv(aq, wqk[0][2 * kk], b[kk & 1][0], b[kk & 1][1]);
                    mma_nv(ak, wqk[1][2 * kk], b[kk & 1][0], b[kk & 1][1]);
                    mma_nv(av, wv[kk & 1][0], b[kk & 1][0], b[kk & 1][1]);
                    mma_nv(aq, wqk[0][2 * kk + 1], b[kk & 1][2], b[kk & 1][3]);
                    mma_nv(ak, wqk[1][2 * kk + 1], b[kk & 1][2], b[kk & 1][3]);
                    mma_nv(av, wv[kk & 1][1], b[kk & 1][2], b[kk & 1][3]);
                }
                TSX(2);
                float gv[6], kp[6];
#pragma unroll
                for (int i = 0; i < 4; i++) {
                    gv[i] = kh == 0 ? ak[i] : aq[i];
                    kp[i] = kh == 0 ? aq[i] : ak[i];
                }
                gv[4] = kh == 0 ? av[2] : av[0]; gv[5] = kh == 0 ? av[3] : av[1];
                kp[4] = kh == 0 ? av[0] : av[2]; kp[5] = kh == 0 ? av[1] : av[3];
                asm volatile("st.shared.v4.f32 [%0], {%1,%2,%3,%4};" :: "r"(redMine), "f"(gv[0]), "f"(gv[1]), "f"(gv[2]), "f"(gv[3]) : "memory");
                asm volatile("st.shared.v2.f32 [%0], {%1,%2};" :: "r"(redMineV), "f"(gv[4]), "f"(gv[5]) : "memory");
                named_bar_sync(1 + g, 64);
                float o0, o1, o2, o3, o4, o5;
                asm volatile("ld.shared.v4.f32 {%0,%1,%2,%3}, [%4];" : "=f"(o0), "=f"(o1), "=f"(o2), "=f"(o3) : "r"(redOther) : "memory");
                asm volatile("ld.shared.v2.f32 {%0,%1}, [%2];" : "=f"(o4), "=f"(o5) : "r"(redOtherV) : "memory");
                uint32_t r0 = pack_bf16(kp[0] + o0, kp[1] + o1);
                uint32_t r1 = pack_bf16(kp[2] + o2, kp[3] + o3);
                uint32_t r2 = pack_bf16(kp[4] + o4, kp[5] + o5);
                asm volatile("stmatrix.sync.aligned.m8n8.x2.trans.shared.b16 [%0], {%1,%2};" :: "r"(kh == 0 ? qDst : sKV + kvOff), "r"(r0), "r"(r1) : "memory");
                const uint32_t vAddr = sKV + 5120 + half * 5120 + lr * 128 + (((g * 2 + kh) ^ lr) << 4);
                asm volatile("stmatrix.sync.aligned.m8n8.x1.trans.shared.b16 [%0], {%1};" :: "r"(vAddr), "r"(r2) : "memory");
                named_bar_arrive(5, 384);
                TSX(3);
                __syncwarp();
                if (lane < 8) {
                    uint32_t f[4];
                    lds128(f, vAddr);
                    st_async_v4(vAddr + peerBase, f[0], f[1], f[2], f[3], barV + peerBase);
                }
            }
            if (s == NSTEPS - 1) break;
            named_bar_sync(10, 384);
#pragma unroll
            for (int i = 8; i < 16; i++) {
                lds128(wo[i], wobase + i * 512);
            }
            TSX(4);
            named_bar_sync(8, 384);
            TSX(5);
            const uint32_t tag = ((s >> 1) + 1) & 1;
            const uint32_t slotOff = (s & 1) * (64 * 256);
            {
                float a2[2][2][4];
#pragma unroll
                for (int i = 0; i < 4; i++) { a2[0][0][i] = a2[0][1][i] = a2[1][0][i] = a2[1][1][i] = 0.f; }
                uint32_t b[4][4];
#pragma unroll
                for (int kk = 0; kk < 4; kk++) ldmatrix_x4(b[kk][0], b[kk][1], b[kk][2], b[kk][3], oAddr + kk * 64);
#pragma unroll
                for (int kk = 0; kk < 4; kk++) {
                    mma_nv(a2[0][0], wo[kk * 4 + 0], b[kk][0], b[kk][1]);
                    mma_nv(a2[1][0], wo[kk * 4 + 1], b[kk][0], b[kk][1]);
                    mma_nv(a2[0][1], wo[kk * 4 + 2], b[kk][2], b[kk][3]);
                    mma_nv(a2[1][1], wo[kk * 4 + 3], b[kk][2], b[kk][3]);
                }
                st_async_v4(rsDst, pack_bf16(a2[0][0][0] + a2[0][1][0], a2[0][0][1] + a2[0][1][1]), pack_bf16(a2[0][0][2] + a2[0][1][2], a2[0][0][3] + a2[0][1][3]),
                            pack_bf16(a2[1][0][0] + a2[1][1][0], a2[1][0][1] + a2[1][1][1]), pack_bf16(a2[1][0][2] + a2[1][1][2], a2[1][0][3] + a2[1][1][3]), rsBar);
            }
            TSX(6);
            if (warp < 2) {
                mbar_wait(barRS, s & 1);
                TSX(7);
                uint32_t u[8][2];
#pragma unroll
                for (int h = 0; h < 8; h++)
                    asm volatile("ld.shared.v2.u32 {%0,%1}, [%2];" : "=r"(u[h][0]), "=r"(u[h][1]) : "r"(sb + CH_OFF_RS + h * 512 + lane * 16 + warp * 8) : "memory");
                if (tid == 0) mbar_expect_tx(barRS, 4096);
                float f0 = 0.f, f1 = 0.f, f2 = 0.f, f3 = 0.f;
                {
                    float a[8], b[8], c[8], d[8];
#pragma unroll
                    for (int h = 0; h < 8; h++) {
                        a[h] = __uint_as_float(u[h][0] << 16); b[h] = __uint_as_float(u[h][0] & 0xffff0000u);
                        c[h] = __uint_as_float(u[h][1] << 16); d[h] = __uint_as_float(u[h][1] & 0xffff0000u);
                    }
                    f0 = ((a[0] + a[1]) + (a[2] + a[3])) + ((a[4] + a[5]) + (a[6] + a[7]));
                    f1 = ((b[0] + b[1]) + (b[2] + b[3])) + ((b[4] + b[5]) + (b[6] + b[7]));
                    f2 = ((c[0] + c[1]) + (c[2] + c[3])) + ((c[4] + c[5]) + (c[6] + c[7]));
                    f3 = ((d[0] + d[1]) + (d[2] + d[3])) + ((d[4] + d[5]) + (d[6] + d[7]));
                }
                const uint32_t x0 = (__float_as_uint(f0) & ~1u) | tag;
                st_relaxed_v4(llW + slotOff, x0, __float_as_uint(f1), __float_as_uint(f2), __float_as_uint(f3));
                const float* r1 = p.part + slotOff + ((size_t)((cl ^ 1) * 16 + rank) * 64 + tid) * 4;
                const float* r2 = p.part + slotOff + ((size_t)((cl ^ 2) * 16 + rank) * 64 + tid) * 4;
                const float* r3 = p.part + slotOff + ((size_t)((cl ^ 3) * 16 + rank) * 64 + tid) * 4;
                uint4 v1, v2, v3;
                uint32_t n = 0;
                do { v1 = ld_relaxed_v4(r1); v2 = ld_relaxed_v4(r2); v3 = ld_relaxed_v4(r3); }
                while (POLL_R && (((v1.x ^ tag) | (v2.x ^ tag) | (v3.x ^ tag)) & 1u) && ++n < (1u << 22));
                TSX(8);
                f0 = (__uint_as_float(x0) + __uint_as_float(v1.x)) + (__uint_as_float(v2.x) + __uint_as_float(v3.x));
                f1 = (f1 + __uint_as_float(v1.y)) + (__uint_as_float(v2.y) + __uint_as_float(v3.y));
                f2 = (f2 + __uint_as_float(v1.z)) + (__uint_as_float(v2.z) + __uint_as_float(v3.z));
                f3 = (f3 + __uint_as_float(v1.w)) + (__uint_as_float(v2.w) + __uint_as_float(v3.w));
                const int ch = warp * 2 + (lm & 1);
                asm volatile("stmatrix.sync.aligned.m8n8.x2.trans.shared.b16 [%0], {%1,%2};"
                             :: "r"(sb + CH_OFF_STG + lr * 64 + ((ch ^ ((lr >> 1) & 3)) << 4)), "r"(pack_bf16(f0, f1)), "r"(pack_bf16(f2, f3)) : "memory");
                named_bar_sync(9, 64);
                uint32_t f[4];
                lds128(f, sb + CH_OFF_STG + lane * 16);
                const uint32_t dst0 = sb + CH_OFF_MEM + (half * 8 + (rank >> 1)) * 512 + lane * 16;
#pragma unroll
                for (int d = 0; d < 8; d++) {
                    const uint32_t dr = warp * 8 + d;
                    st_async_v4(mapa_u32(dst0, dr), f[0], f[1], f[2], f[3], mapa_u32(barMem, dr));
                }
                TSX(9);
            }
        }
    } else {
        reg_dealloc<88>();
        const int aw = warp - 8;
        const uint32_t peerBase = mapa_u32(sb, peer) - sb;
        const float sm_scale = 0.08838834764831845f * 1.4426950408889634f;
        const int kc64 = 64 + head * 2 + half, vc64 = 128 + head * 2;
        auto issue_kv = [&](int s) {
            if ((s & 3) == 0) {
                uint32_t n = 0;
                while (ld_acquire_u32(p.flags + (s >> 2)) < p.flag_target) { if (++n > (1u << 22)) break; }
                fence_proxy_async_all();
            }
            int st = s & (CH_NKV - 1);
            uint32_t base = sb + CH_OFF_KV + st * CH_KV_BYTES;
            mbar_expect_tx(barKV + 8 * st, 12288);
            tma_load_3d(base + 1024, &p.tmKV, 0, s * 32, kc64, barKV + 8 * st);
            tma_load_3d(base + 5120 + 1024, &p.tmKV, 0, s * 32, vc64, barKV + 8 * st);
            tma_load_3d(base + 10240 + 1024, &p.tmKV, 0, s * 32, vc64 + 1, barKV + 8 * st);
        };
        if (aw == 3 && lane == 0) { for (int s = 0; s < CH_NKV - 1; s++) issue_kv(s); }
        const uint32_t kOff0 = lr * 128 + ((lm ^ lr) << 4), kOff1 = lr * 128 + (((4 + lm) ^ lr) << 4);
        const uint32_t qAddr = (lm & 1) ? (sb + CH_OFF_ZERO) : (sb + CH_OFF_Q + lr * CH_Q_STRIDE + (lm >> 1) * 16);
        const uint32_t qStep = (lm & 1) ? 0u : 32u;
        const uint32_t vRow = ((lm >> 1) * 8 + lr) * 128;
        const uint32_t vOff0 = 5120 + (aw >> 1) * 5120 + vRow + ((((aw & 1) * 4 + (lm & 1)) ^ lr) << 4);
        const uint32_t vOff1 = 5120 + (aw >> 1) * 5120 + vRow + ((((aw & 1) * 4 + 2 + (lm & 1)) ^ lr) << 4);
        const uint32_t padAdj = (lm >> 1) ? 2048u : 0u;
        const uint32_t scAddr = sb + CH_OFF_SC + lane * 8;
        const uint32_t oDst = sb + CH_OFF_O + lr * CH_O_STRIDE + (aw * 32 + lm * 8) * 2;
        const int si = tid - 256, sw = si >> 6, stok = (si >> 3) & 7, scn = si & 7;
        const uint32_t kvmOff = (sw == 0 ? 0u : 5120u + half * 5120u) + stok * 128 + ((scn ^ stok) << 4);
        bf16* kvmDst = p.kvmem + (size_t)stok * 8192 + sw * 4096 + head * 128 + half * 64 + scn * 8;
        const bool leader = (tid == 256);
        for (int s = 0; s < NSTEPS; s++) {
            const uint32_t par = s & 1;
            const int st = s & (CH_NKV - 1);
            const uint32_t sKV = sb + CH_OFF_KV + st * CH_KV_BYTES;
            mbar_wait(barKV + 8 * st, (s / CH_NKV) & 1);
            uint32_t kb[2][4][4], va[3][2][4];
#pragma unroll
            for (int n = 0; n < 4; n++) {
                ldmatrix_x4(kb[0][n][0], kb[0][n][1], kb[0][n][2], kb[0][n][3], sKV + (n + 1) * 1024 + kOff0);
                ldmatrix_x4(kb[1][n][0], kb[1][n][1], kb[1][n][2], kb[1][n][3], sKV + (n + 1) * 1024 + kOff1);
            }
            TSX(0);
            named_bar_sync(5, 384);
            TSX(1);
            float sc[5][4];
#pragma unroll
            for (int n = 0; n < 5; n++) { sc[n][0] = sc[n][1] = sc[n][2] = sc[n][3] = 0.f; }
            {
                uint32_t a[4][4], km[2][4];
#pragma unroll
                for (int k = 0; k < 4; k++) ldmatrix_x4(a[k][0], a[k][1], a[k][2], a[k][3], qAddr + k * qStep);
                ldmatrix_x4(km[0][0], km[0][1], km[0][2], km[0][3], sKV + kOff0);
                ldmatrix_x4(km[1][0], km[1][1], km[1][2], km[1][3], sKV + kOff1);
#pragma unroll
                for (int kp = 0; kp < 2; kp++) {
#pragma unroll
                    for (int n = 0; n < 4; n++) mma_nv(sc[n + 1], a[kp * 2], kb[kp][n][0], kb[kp][n][1]);
#pragma unroll
                    for (int n = 0; n < 4; n++) mma_nv(sc[n + 1], a[kp * 2 + 1], kb[kp][n][2], kb[kp][n][3]);
                }
                mma_nv(sc[0], a[0], km[0][0], km[0][1]);
                mma_nv(sc[0], a[1], km[0][2], km[0][3]);
                mma_nv(sc[0], a[2], km[1][0], km[1][1]);
                mma_nv(sc[0], a[3], km[1][2], km[1][3]);
            }
            TSX(2);
            if (aw == 0) {
#pragma unroll
                for (int n = 0; n < 5; n++) st_async_v2(scAddr + peerBase + n * 256, __float_as_uint(sc[n][0]), __float_as_uint(sc[n][1]), barSc + peerBase);
            }
#pragma unroll
            for (int ks = 1; ks < 3; ks++) {
                const uint32_t adj = ks == 2 ? padAdj : 0u;
                ldmatrix_x4_t(va[ks][0][0], va[ks][0][1], va[ks][0][2], va[ks][0][3], sKV + ks * 2048 + vOff0 - adj);
                ldmatrix_x4_t(va[ks][1][0], va[ks][1][1], va[ks][1][2], va[ks][1][3], sKV + ks * 2048 + vOff1 - adj);
            }
            uint4 kvm;
            if (sw == 0) asm volatile("ld.shared.v4.u32 {%0,%1,%2,%3}, [%4];" : "=r"(kvm.x), "=r"(kvm.y), "=r"(kvm.z), "=r"(kvm.w) : "r"(sKV + kvmOff) : "memory");
            TSX(3);
            mbar_wait(barSc, par);
            TSX(4);
            float pp[5][2];
#pragma unroll
            for (int n = 0; n < 5; n++)
                asm volatile("ld.shared.v2.f32 {%0,%1}, [%2];" : "=f"(pp[n][0]), "=f"(pp[n][1]) : "r"(scAddr + n * 256) : "memory");
            if (leader) mbar_expect_tx(barSc, 1280);
#pragma unroll
            for (int n = 0; n < 5; n++) { sc[n][0] += pp[n][0]; sc[n][1] += pp[n][1]; }
            float mx = fmaxf(fmaxf(fmaxf(sc[0][0], sc[0][1]), fmaxf(sc[1][0], sc[1][1])), fmaxf(fmaxf(sc[2][0], sc[2][1]), fmaxf(sc[3][0], sc[3][1])));
            mx = fmaxf(mx, fmaxf(sc[4][0], sc[4][1]));
            mx = fmaxf(mx, __shfl_xor_sync(0xffffffff, mx, 1));
            mx = fmaxf(mx, __shfl_xor_sync(0xffffffff, mx, 2));
            const float mb = mx * sm_scale;
            uint32_t pb[5];
#pragma unroll
            for (int n = 0; n < 5; n++)
                pb[n] = pack_bf16(ex2_approx(fmaf(sc[n][0], sm_scale, -mb)), ex2_approx(fmaf(sc[n][1], sm_scale, -mb)));
            if (s < NSTEPS - 1) named_bar_arrive(10, 384);
            TSX(5);
            float oc[2][4];
#pragma unroll
            for (int i = 0; i < 4; i++) { oc[0][i] = oc[1][i] = 0.f; }
            mma_nv(oc[0], va[1][0], pb[2], pb[3]);
            mma_nv(oc[1], va[1][1], pb[2], pb[3]);
            mma_nv(oc[0], va[2][0], pb[4], 0u);
            mma_nv(oc[1], va[2][1], pb[4], 0u);
            float sm[4] = {0.f, 0.f, 0.f, 0.f};
            {
                const uint32_t ones[4] = {0x3F803F80u, 0x3F803F80u, 0x3F803F80u, 0x3F803F80u};
                mma_nv(sm, ones, pb[0], pb[1]);
                mma_nv(sm, ones, pb[2], pb[3]);
                mma_nv(sm, ones, pb[4], 0u);
            }
            const float i0 = __fdividef(1.0f, sm[0]), i1 = __fdividef(1.0f, sm[1]);
            TSX(6);
            mbar_wait(barV, par);
            TSX(7);
            ldmatrix_x4_t(va[0][0][0], va[0][0][1], va[0][0][2], va[0][0][3], sKV + vOff0);
            ldmatrix_x4_t(va[0][1][0], va[0][1][1], va[0][1][2], va[0][1][3], sKV + vOff1);
            if (leader) mbar_expect_tx(barV, 1024);
            if (sw == 1) asm volatile("ld.shared.v4.u32 {%0,%1,%2,%3}, [%4];" : "=r"(kvm.x), "=r"(kvm.y), "=r"(kvm.z), "=r"(kvm.w) : "r"(sKV + kvmOff) : "memory");
            mma_nv(oc[0], va[0][0], pb[0], pb[1]);
            mma_nv(oc[1], va[0][1], pb[0], pb[1]);
            stmatrix_x4_t(oDst, pack_bf16(oc[0][0] * i0, oc[0][1] * i1), pack_bf16(oc[0][2] * i0, oc[0][3] * i1),
                          pack_bf16(oc[1][0] * i0, oc[1][1] * i1), pack_bf16(oc[1][2] * i0, oc[1][3] * i1));
            if (s < NSTEPS - 1) named_bar_arrive(8, 384);
            TSX(8);
            *reinterpret_cast<uint4*>(kvmDst + (size_t)s * 65536) = kvm;
            if (p.seg_flags) { named_bar_sync(11, 128); if (leader) { __threadfence(); atomicAdd(p.seg_flags + s * 32, 1u); } }
            if (aw == 3 && lane == 0 && s + CH_NKV - 1 < NSTEPS) issue_kv(s + CH_NKV - 1);
        }
    }
    __syncthreads();
    TL_END(0);
    cluster_sync_all();
}

struct AttnAParams {
    CUtensorMap tmKV;
    const bf16* qkv;
    bf16* o;
};
constexpr int AA_KT = 256;
constexpr int AA_NST = 3;
constexpr int AA_SMEM = AA_NST * 2 * AA_KT * 32 + 64;

__device__ __forceinline__ float ex2a(float x) { float y; asm("ex2.approx.ftz.f32 %0, %1;" : "=f"(y) : "f"(x)); return y; }
__device__ __forceinline__ void mma_f(float* c, const uint32_t* a, uint32_t b0, uint32_t b1) {
    asm("mma.sync.aligned.m16n8k16.row.col.f32.bf16.bf16.f32 {%0,%1,%2,%3}, {%4,%5,%6,%7}, {%8,%9}, {%0,%1,%2,%3};"
        : "+f"(c[0]), "+f"(c[1]), "+f"(c[2]), "+f"(c[3]) : "r"(a[0]), "r"(a[1]), "r"(a[2]), "r"(a[3]), "r"(b0), "r"(b1));
}

__global__ void __launch_bounds__(256, 2) attn_a_kernel(const __grid_constant__ AttnAParams p) {
    extern __shared__ __align__(1024) unsigned char smem[];
    const uint32_t sb = smem_u32(smem);
    const uint32_t bars = sb + AA_NST * 2 * AA_KT * 32;
    const int tid = threadIdx.x, lane = tid & 31, warp = tid >> 5;
    const int head = blockIdx.x >> 3, qt = blockIdx.x & 7;
    const int t4 = lane & 3, g8 = lane >> 2;
    constexpr int NT = 2048 / AA_KT;
    TL_START(4);

    if (tid == 0) {
        for (int i = 0; i < AA_NST; i++) { mbar_init(bars + 8 * i, 1); mbar_init(bars + 8 * (AA_NST + i), 8); }
        fence_mbar_init();
    }
    __syncthreads();
    auto issue = [&](int t) {
        int st = t % AA_NST;
        uint32_t dst = sb + st * (2 * AA_KT * 32);
        mbar_expect_tx(bars + 8 * st, 2 * AA_KT * 32);
        tma_load_2d(dst, &p.tmKV, 512 + head * 16, t * AA_KT, bars + 8 * st);
        tma_load_2d(dst + AA_KT * 32, &p.tmKV, 1024 + head * 16, t * AA_KT, bars + 8 * st);
    };
    if (tid == 0) { for (int t = 0; t < AA_NST; t++) issue(t); }

    uint32_t qa[2][4];
    const int row0 = qt * 256 + warp * 32;
#pragma unroll
    for (int m = 0; m < 2; m++) {
        const bf16* q = p.qkv + (size_t)(row0 + m * 16 + g8) * 1536 + head * 16 + t4 * 2;
        qa[m][0] = *reinterpret_cast<const uint32_t*>(q);
        qa[m][1] = *reinterpret_cast<const uint32_t*>(q + 8 * 1536);
        qa[m][2] = *reinterpret_cast<const uint32_t*>(q + 8);
        qa[m][3] = *reinterpret_cast<const uint32_t*>(q + 8 * 1536 + 8);
    }
    const float sc = 0.25f * 1.4426950408889634f;
    float mrow[2][2], oacc[2][2][4], lacc[2][4];
#pragma unroll
    for (int m = 0; m < 2; m++) {
        mrow[m][0] = mrow[m][1] = -3.0e38f;
#pragma unroll
        for (int i = 0; i < 4; i++) { oacc[m][0][i] = oacc[m][1][i] = 0.f; lacc[m][i] = 0.f; }
    }
    const uint32_t ones = 0x3F803F80u;
    const int lr = lane & 7, lm = lane >> 3;
    const int krow = (lm >> 1) * 8 + lr, kch = lm & 1;
    const uint32_t koff = krow * 32 + ((kch ^ ((krow >> 2) & 1)) << 4);
    const int vrow = (lm & 1) * 8 + lr, vch = lm >> 1;
    const uint32_t voff = vrow * 32 + ((vch ^ ((vrow >> 2) & 1)) << 4);

    for (int t = 0; t < NT; t++) {
        const int st = t % AA_NST;
        mbar_wait(bars + 8 * st, (t / AA_NST) & 1);
        const uint32_t sK = sb + st * (2 * AA_KT * 32), sV = sK + AA_KT * 32;
#pragma unroll 1
        for (int kb = 0; kb < AA_KT / 64; kb++) {
            float s[2][8][4];
#pragma unroll
            for (int np = 0; np < 4; np++) {
                uint32_t b0, b1, b2, b3;
                ldmatrix_x4(b0, b1, b2, b3, sK + (kb * 64 + np * 16) * 32 + koff);
#pragma unroll
                for (int m = 0; m < 2; m++) {
#pragma unroll
                    for (int i = 0; i < 4; i++) { s[m][np * 2][i] = 0.f; s[m][np * 2 + 1][i] = 0.f; }
                    mma_f(s[m][np * 2], qa[m], b0, b1);
                    mma_f(s[m][np * 2 + 1], qa[m], b2, b3);
                }
            }
            uint32_t pa[2][4][4];
#pragma unroll
            for (int m = 0; m < 2; m++) {
                float mx0 = s[m][0][0], mx1 = s[m][0][2];
#pragma unroll
                for (int n = 0; n < 8; n++) {
                    mx0 = fmaxf(mx0, fmaxf(s[m][n][0], s[m][n][1]));
                    mx1 = fmaxf(mx1, fmaxf(s[m][n][2], s[m][n][3]));
                }
                mx0 = fmaxf(mx0, __shfl_xor_sync(0xffffffff, mx0, 1)); mx0 = fmaxf(mx0, __shfl_xor_sync(0xffffffff, mx0, 2));
                mx1 = fmaxf(mx1, __shfl_xor_sync(0xffffffff, mx1, 1)); mx1 = fmaxf(mx1, __shfl_xor_sync(0xffffffff, mx1, 2));
                const float mn0 = fmaxf(mrow[m][0], mx0), mn1 = fmaxf(mrow[m][1], mx1);
                const float a0 = ex2a((mrow[m][0] - mn0) * sc), a1 = ex2a((mrow[m][1] - mn1) * sc);
                mrow[m][0] = mn0; mrow[m][1] = mn1;
                const float mb0 = mn0 * sc, mb1 = mn1 * sc;
#pragma unroll
                for (int d = 0; d < 2; d++) { oacc[m][d][0] *= a0; oacc[m][d][1] *= a0; oacc[m][d][2] *= a1; oacc[m][d][3] *= a1; }
                lacc[m][0] *= a0; lacc[m][2] *= a1;
#pragma unroll
                for (int n = 0; n < 8; n++) {
                    float p0 = ex2a(fmaf(s[m][n][0], sc, -mb0)), p1 = ex2a(fmaf(s[m][n][1], sc, -mb0));
                    float p2 = ex2a(fmaf(s[m][n][2], sc, -mb1)), p3 = ex2a(fmaf(s[m][n][3], sc, -mb1));
                    pa[m][n >> 1][(n & 1) * 2 + 0] = pack_bf16(p0, p1);
                    pa[m][n >> 1][(n & 1) * 2 + 1] = pack_bf16(p2, p3);
                }
            }
#pragma unroll
            for (int ks = 0; ks < 4; ks++) {
                uint32_t b0, b1, b2, b3;
                ldmatrix_x4_t(b0, b1, b2, b3, sV + (kb * 64 + ks * 16) * 32 + voff);
#pragma unroll
                for (int m = 0; m < 2; m++) {
                    mma_f(oacc[m][0], pa[m][ks], b0, b1);
                    mma_f(oacc[m][1], pa[m][ks], b2, b3);
                    mma_f(lacc[m], pa[m][ks], ones, ones);
                }
            }
        }
        __syncwarp();
        if (lane == 0) mbar_arrive(bars + 8 * (AA_NST + st));
        if (tid == 0 && t + AA_NST < NT) {
            mbar_wait(bars + 8 * (AA_NST + st), (t / AA_NST) & 1);
            issue(t + AA_NST);
        }
    }
#pragma unroll
    for (int m = 0; m < 2; m++) {
        const float i0 = 1.0f / lacc[m][0], i1 = 1.0f / lacc[m][2];
        bf16* o = p.o + (size_t)(row0 + m * 16 + g8) * 512 + head * 16 + t4 * 2;
#pragma unroll
        for (int d = 0; d < 2; d++) {
            *reinterpret_cast<uint32_t*>(o + d * 8) = pack_bf16(oacc[m][d][0] * i0, oacc[m][d][1] * i0);
            *reinterpret_cast<uint32_t*>(o + 8 * 512 + d * 8) = pack_bf16(oacc[m][d][2] * i1, oacc[m][d][3] * i1);
        }
    }
    TL_END(4);
}

struct AttnBParams {
    CUtensorMap tmQKV;
    CUtensorMap tmKVM;
    CUtensorMap tmO;
    const unsigned int* seg_flags;
    unsigned int seg_target;
    unsigned int* tile_flags;
};
constexpr int AB_WARP_BYTES = 28672;
constexpr int AB_SMEM = 4 * AB_WARP_BYTES + 64;

__global__ void __launch_bounds__(128, 2) attn_b_kernel(const __grid_constant__ AttnBParams p) {
    extern __shared__ __align__(1024) unsigned char smem[];
    const int tid = threadIdx.x, lane = tid & 31, warp = tid >> 5;
    const uint32_t sb = smem_u32(smem) + warp * AB_WARP_BYTES;
    const uint32_t bar = smem_u32(smem) + 4 * AB_WARP_BYTES + warp * 8;
    const int t4 = lane & 3, g8 = lane >> 2;
    TL_START(6);
    if (lane == 0) { mbar_init(bar, 1); fence_mbar_init(); }
    __syncwarp();
    uint32_t phase = 0;
    for (int task = blockIdx.x; task < 512; task += gridDim.x, phase ^= 1) {
    const int seg = task >> 3, head = (task & 7) * 4 + warp;
    const uint32_t sQ = sb, sK = sb + 8192, sV = sb + 16384, sKm = sb + 24576, sVm = sb + 26624;
    if (tid == 0 && p.seg_flags) {
        uint32_t n = 0;
        while (ld_acquire_u32(p.seg_flags + seg * 32) < p.seg_target) { if (++n > (1u << 22)) break; __nanosleep(1000); }
    }
    __syncthreads();
    if (lane == 0) {
        fence_proxy_async_all();
        mbar_expect_tx(bar, AB_WARP_BYTES);
#pragma unroll
        for (int h = 0; h < 2; h++) {
            tma_load_3d(sQ + h * 4096, &p.tmQKV, 0, seg * 32, head * 2 + h, bar);
            tma_load_3d(sK + h * 4096, &p.tmQKV, 0, seg * 32, 64 + head * 2 + h, bar);
            tma_load_3d(sV + h * 4096, &p.tmQKV, 0, seg * 32, 128 + head * 2 + h, bar);
            tma_load_3d(sKm + h * 1024, &p.tmKVM, 0, seg * 8, head * 2 + h, bar);
            tma_load_3d(sVm + h * 1024, &p.tmKVM, 0, seg * 8, 64 + head * 2 + h, bar);
        }
    }
    __syncwarp();
    mbar_wait(bar, phase);
    const int lr = lane & 7, lm = lane >> 3;
    float s[2][5][4];
#pragma unroll
    for (int m = 0; m < 2; m++)
#pragma unroll
        for (int n = 0; n < 5; n++)
#pragma unroll
            for (int i = 0; i < 4; i++) s[m][n][i] = 0.f;
#pragma unroll
    for (int kp = 0; kp < 4; kp++) {
        const int hb = kp >> 1, c0 = (kp & 1) * 4;
        uint32_t a[2][2][4];
#pragma unroll
        for (int m = 0; m < 2; m++)
#pragma unroll
            for (int ks = 0; ks < 2; ks++) {
                int row = m * 16 + (lm & 1) * 8 + lr, ch = c0 + ks * 2 + (lm >> 1);
                ldmatrix_x4(a[m][ks][0], a[m][ks][1], a[m][ks][2], a[m][ks][3], sQ + hb * 4096 + row * 128 + ((ch ^ (row & 7)) << 4));
            }
#pragma unroll
        for (int n = 0; n < 5; n++) {
            uint32_t b0, b1, b2, b3;
            int ch = c0 + lm;
            if (n == 0) ldmatrix_x4(b0, b1, b2, b3, sKm + hb * 1024 + lr * 128 + ((ch ^ lr) << 4));
            else { int row = (n - 1) * 8 + lr; ldmatrix_x4(b0, b1, b2, b3, sK + hb * 4096 + row * 128 + ((ch ^ (row & 7)) << 4)); }
#pragma unroll
            for (int m = 0; m < 2; m++) { mma_f(s[m][n], a[m][0], b0, b1); mma_f(s[m][n], a[m][1], b2, b3); }
        }
    }
    const float sc = 0.08838834764831845f * 1.4426950408889634f;
    uint32_t pa[2][3][4];
    float inv[2][2];
#pragma unroll
    for (int m = 0; m < 2; m++) {
        const int r0 = m * 16 + g8, r1 = r0 + 8;
        float mx0 = -3.0e38f, mx1 = -3.0e38f;
#pragma unroll
        for (int n = 0; n < 5; n++) {
            if (n > 0) {
                int j = (n - 1) * 8 + t4 * 2;
                if (j > r0) s[m][n][0] = -3.0e38f;
                if (j + 1 > r0) s[m][n][1] = -3.0e38f;
                if (j > r1) s[m][n][2] = -3.0e38f;
                if (j + 1 > r1) s[m][n][3] = -3.0e38f;
            }
            mx0 = fmaxf(mx0, fmaxf(s[m][n][0], s[m][n][1]));
            mx1 = fmaxf(mx1, fmaxf(s[m][n][2], s[m][n][3]));
        }
        mx0 = fmaxf(mx0, __shfl_xor_sync(0xffffffff, mx0, 1)); mx0 = fmaxf(mx0, __shfl_xor_sync(0xffffffff, mx0, 2));
        mx1 = fmaxf(mx1, __shfl_xor_sync(0xffffffff, mx1, 1)); mx1 = fmaxf(mx1, __shfl_xor_sync(0xffffffff, mx1, 2));
        const float mb0 = mx0 * sc, mb1 = mx1 * sc;
        float l0 = 0.f, l1 = 0.f;
#pragma unroll
        for (int n = 0; n < 5; n++) {
            s[m][n][0] = ex2a(fmaf(s[m][n][0], sc, -mb0)); s[m][n][1] = ex2a(fmaf(s[m][n][1], sc, -mb0));
            s[m][n][2] = ex2a(fmaf(s[m][n][2], sc, -mb1)); s[m][n][3] = ex2a(fmaf(s[m][n][3], sc, -mb1));
            l0 += s[m][n][0] + s[m][n][1]; l1 += s[m][n][2] + s[m][n][3];
        }
        l0 += __shfl_xor_sync(0xffffffff, l0, 1); l0 += __shfl_xor_sync(0xffffffff, l0, 2);
        l1 += __shfl_xor_sync(0xffffffff, l1, 1); l1 += __shfl_xor_sync(0xffffffff, l1, 2);
        inv[m][0] = 1.0f / l0; inv[m][1] = 1.0f / l1;
#pragma unroll
        for (int n = 0; n < 5; n++) {
            pa[m][n >> 1][(n & 1) * 2 + 0] = pack_bf16(s[m][n][0] * inv[m][0], s[m][n][1] * inv[m][0]);
            pa[m][n >> 1][(n & 1) * 2 + 1] = pack_bf16(s[m][n][2] * inv[m][1], s[m][n][3] * inv[m][1]);
        }
        pa[m][2][2] = 0u; pa[m][2][3] = 0u;
    }
    __syncwarp();
#pragma unroll
    for (int dq = 0; dq < 4; dq++) {
        float oc[2][4][4];
#pragma unroll
        for (int m = 0; m < 2; m++)
#pragma unroll
            for (int n = 0; n < 4; n++)
#pragma unroll
                for (int i = 0; i < 4; i++) oc[m][n][i] = 0.f;
        const int hb = dq >> 1, c0 = (dq & 1) * 4;
#pragma unroll
        for (int ks = 0; ks < 3; ks++) {
#pragma unroll
            for (int dp = 0; dp < 2; dp++) {
                int key = ks * 16 + (lm & 1) * 8 + lr, ch = c0 + dp * 2 + (lm >> 1);
                uint32_t addr;
                if (key < 8 || key >= 40) addr = sVm + hb * 1024 + lr * 128 + ((ch ^ lr) << 4);
                else { int row = key - 8; addr = sV + hb * 4096 + row * 128 + ((ch ^ (row & 7)) << 4); }
                uint32_t b0, b1, b2, b3;
                ldmatrix_x4_t(b0, b1, b2, b3, addr);
#pragma unroll
                for (int m = 0; m < 2; m++) { mma_f(oc[m][dp * 2], pa[m][ks], b0, b1); mma_f(oc[m][dp * 2 + 1], pa[m][ks], b2, b3); }
            }
        }
#pragma unroll
        for (int m = 0; m < 2; m++)
#pragma unroll
            for (int dp = 0; dp < 2; dp++) {
                int row = m * 16 + (lm & 1) * 8 + lr, ch = c0 + dp * 2 + (lm >> 1);
                stmatrix_x4(sQ + hb * 4096 + row * 128 + ((ch ^ (row & 7)) << 4),
                            pack_bf16(oc[m][dp * 2][0], oc[m][dp * 2][1]), pack_bf16(oc[m][dp * 2][2], oc[m][dp * 2][3]),
                            pack_bf16(oc[m][dp * 2 + 1][0], oc[m][dp * 2 + 1][1]), pack_bf16(oc[m][dp * 2 + 1][2], oc[m][dp * 2 + 1][3]));
            }
    }
    fence_proxy_async_smem();
    __syncwarp();
    if (lane == 0) {
        tma_store_3d(&p.tmO, sQ, 0, seg * 32, head * 2);
        tma_store_3d(&p.tmO, sQ + 4096, 0, seg * 32, head * 2 + 1);
        bulk_commit();
        bulk_wait_all0();
        fence_proxy_async_all();
        __threadfence();
        atomicAdd(p.tile_flags + (seg >> 2), 1u);
    }
    __syncwarp();
    }
    TL_END(6);
}

struct GemmSParams {
    CUtensorMap tmA;
    CUtensorMap tmB;
    CUtensorMap tmC;
    int n_tiles;
    int m_tiles;
    bf16* c; int ldc;
    int kblocks_half;
    int c_col64;
    const unsigned int* tile_flags;
    unsigned int tile_target;
};
constexpr int GS_NST = 5;
constexpr int GS_SMEM = GS_NST * 32768 + 32768 + 256;

__global__ void __launch_bounds__(288, 1) gemm_s_kernel(const __grid_constant__ GemmSParams p) {
    extern __shared__ __align__(1024) unsigned char smem[];
    const uint32_t sS = smem_u32(smem);
    const uint32_t sR = sS + GS_NST * 32768;
    const uint32_t bars = sR + 32768;
    const uint32_t barFull = bars, barEmpty = bars + 8 * GS_NST, barRed = bars + 16 * GS_NST, barFree = barRed + 8;
    const int warp = __shfl_sync(0xffffffff, threadIdx.x >> 5, 0), lane = threadIdx.x & 31;
    const int kh = blockIdx.x & 1;
    const int ntiles = p.m_tiles * p.n_tiles, ncl = gridDim.x >> 1;
    TL_START(7);
    if (threadIdx.x == 0) {
        for (int i = 0; i < GS_NST; i++) { mbar_init(barFull + 8 * i, 1); mbar_init(barEmpty + 8 * i, 8); }
        mbar_init(barRed, 1);
        mbar_init(barFree, 1);
        fence_mbar_init();
        mbar_expect_tx(barRed, 32768);
    }
    __syncthreads();
    cluster_sync_all();
    if (warp == 8) {
        if (lane == 0) {
            int it = 0;
            for (int tile = blockIdx.x >> 1; tile < ntiles; tile += ncl) {
                const int mt = tile / p.n_tiles, nt = tile % p.n_tiles;
                {
                    uint32_t n = 0;
                    while (ld_acquire_u32(p.tile_flags + mt) < p.tile_target) { if (++n > (1u << 22)) break; __nanosleep(500); }
                    fence_proxy_async_all();
                }
                for (int i = 0; i < p.kblocks_half; i++, it++) {
                    int slot = it % GS_NST;
                    if (it >= GS_NST) mbar_wait(barEmpty + 8 * slot, ((it / GS_NST) - 1) & 1);
                    mbar_expect_tx(barFull + 8 * slot, 32768);
                    int kb = kh * p.kblocks_half + i;
                    tma_load_3d(sS + slot * 32768, &p.tmA, 0, mt * 128, kb, barFull + 8 * slot);
                    tma_load_3d(sS + slot * 32768 + 16384, &p.tmB, 0, kb * 64, nt * 2, barFull + 8 * slot);
                }
            }
        }
    } else {
        const int wg = warp >> 2, wq = warp & 3;
        const uint32_t peer = kh ^ 1;
        const uint32_t rbuf = mapa_u32(sR, peer), rbar = mapa_u32(barRed, peer), rfree = mapa_u32(barFree, peer);
        const int tw = threadIdx.x;
        int it = 0, nt_done = 0;
        for (int tile = blockIdx.x >> 1; tile < ntiles; tile += ncl, nt_done++) {
            const int mt = tile / p.n_tiles, nt = tile % p.n_tiles;
            float acc[64];
            int prev = 0;
            for (int i = 0; i < p.kblocks_half; i++, it++) {
                int slot = it % GS_NST;
                mbar_wait(barFull + 8 * slot, (it / GS_NST) & 1);
                wg_fence();
                uint64_t da = make_desc(sS + slot * 32768 + wg * 8192, 16, 1024);
                uint64_t db = make_desc(sS + slot * 32768 + 16384, 8192, 1024);
#pragma unroll
                for (int kk = 0; kk < 4; kk++)
                    wgmma_m64n128k16_ss_tb(acc, da + (uint64_t)(kk * 2), db + (uint64_t)(kk * 128), (i | kk) != 0);
                wg_commit();
                if (i > 0) { wg_wait<1>(); if (lane == 0) mbar_arrive(barEmpty + 8 * prev); }
                prev = slot;
            }
            wg_wait<0>();
            if (lane == 0) mbar_arrive(barEmpty + 8 * prev);
            if (nt_done > 0) mbar_wait(barFree, (nt_done - 1) & 1);
#pragma unroll
            for (int j = 0; j < 8; j++) {
                float a[4];
#pragma unroll
                for (int i = 0; i < 4; i++) a[i] = kh == 0 ? acc[(8 + j) * 4 + i] : acc[j * 4 + i];
                st_async_v4(rbuf + (j * 256 + tw) * 16, __float_as_uint(a[0]), __float_as_uint(a[1]), __float_as_uint(a[2]), __float_as_uint(a[3]), rbar);
            }
            mbar_wait(barRed, nt_done & 1);
            uint32_t r[4][4];
#pragma unroll
            for (int c = 0; c < 4; c++)
#pragma unroll
                for (int e = 0; e < 2; e++) {
                    int j = c * 2 + e;
                    float4 v;
                    asm volatile("ld.shared.v4.f32 {%0,%1,%2,%3}, [%4];" : "=f"(v.x), "=f"(v.y), "=f"(v.z), "=f"(v.w) : "r"(sR + (j * 256 + tw) * 16) : "memory");
                    float a[4];
#pragma unroll
                    for (int i = 0; i < 4; i++) a[i] = kh == 0 ? acc[j * 4 + i] : acc[(8 + j) * 4 + i];
                    r[c][e * 2 + 0] = pack_bf16(a[0] + v.x, a[1] + v.y);
                    r[c][e * 2 + 1] = pack_bf16(a[2] + v.z, a[3] + v.w);
                }
            named_bar_sync(1, 256);
            if (tw == 0) {
                mbar_expect_tx(barRed, 32768);
                asm volatile("mbarrier.arrive.release.cluster.shared::cluster.b64 _, [%0];" :: "r"(rfree) : "memory");
            }
            bf16* cbase = p.c + (size_t)(mt * 128 + wg * 64 + wq * 16 + (lane >> 2)) * p.ldc + p.c_col64 * 64 + nt * 128 + kh * 64 + (lane & 3) * 2;
#pragma unroll
            for (int c = 0; c < 4; c++)
#pragma unroll
                for (int e = 0; e < 2; e++) {
                    *reinterpret_cast<uint32_t*>(cbase + (c * 2 + e) * 8) = r[c][e * 2 + 0];
                    *reinterpret_cast<uint32_t*>(cbase + 8 * p.ldc + (c * 2 + e) * 8) = r[c][e * 2 + 1];
                }
        }
    }
    TL_END(7);
    __syncthreads();
    cluster_sync_all();
}

typedef CUresult (*PFN_encodeTiled)(CUtensorMap*, CUtensorMapDataType, cuuint32_t, void*, const cuuint64_t*, const cuuint64_t*,
                                    const cuuint32_t*, const cuuint32_t*, CUtensorMapInterleave, CUtensorMapSwizzle,
                                    CUtensorMapL2promotion, CUtensorMapFloatOOBfill);
static PFN_encodeTiled g_encode = nullptr;
static void init_encode() {
    if (g_encode) return;
    void* fn = nullptr;
    cudaDriverEntryPointQueryResult st;
    cudaGetDriverEntryPoint("cuTensorMapEncodeTiled", &fn, cudaEnableDefault, &st);
    g_encode = (PFN_encodeTiled)fn;
}
static CUtensorMap make_tmap_3d64(const void* ptr, uint64_t rows, uint64_t cols, uint64_t ld, uint32_t box_rows, uint32_t box_c64) {
    CUtensorMap tm;
    cuuint64_t dims[3] = {64, rows, cols / 64};
    cuuint64_t strides[2] = {ld * 2, 128};
    cuuint32_t box[3] = {64, box_rows, box_c64};
    cuuint32_t es[3] = {1, 1, 1};
    g_encode(&tm, CU_TENSOR_MAP_DATA_TYPE_BFLOAT16, 3, (void*)ptr, dims, strides, box, es, CU_TENSOR_MAP_INTERLEAVE_NONE,
             CU_TENSOR_MAP_SWIZZLE_128B, CU_TENSOR_MAP_L2_PROMOTION_L2_128B, CU_TENSOR_MAP_FLOAT_OOB_FILL_NONE);
    return tm;
}

#define AB_GRID 24
#define G4_GRID 12
__device__ __align__(1024) bf16 g_qkvA[2048 * 1536];
__device__ __align__(1024) bf16 g_oA[2048 * 512];
__device__ __align__(1024) bf16 g_qkvB[2048 * 12288];
__device__ __align__(1024) bf16 g_kvmem[64 * 8 * 8192];
__device__ __align__(1024) bf16 g_oB[2048 * 4096];
__device__ __align__(1024) float g_part[2 * 64 * 256];
__device__ __align__(128) unsigned int g_flags[4096];

__global__ void cleanup_kernel() {
    const int i = blockIdx.x * blockDim.x + threadIdx.x;
    const int n = gridDim.x * blockDim.x;
    uint4 z = make_uint4(0, 0, 0, 0);
    for (int k = i; k < 2 * 64 * 64; k += n) reinterpret_cast<uint4*>(g_part)[k] = z;
    if (i < 4096) g_flags[i] = 0u;
}

__global__ void delay_kernel() {}

template <typename T> static T* sym_addr(T& sym) { void* p = nullptr; cudaGetSymbolAddress(&p, sym); return (T*)p; }

extern "C" void kernel_launch(void* const* d_in, const int* in_sizes, int n_in, void* d_out, int out_size) {
    const bf16* A_x = (const bf16*)d_in[0];
    const bf16* A_wqkv = (const bf16*)d_in[1];
    const bf16* A_wo = (const bf16*)d_in[2];
    const bf16* B_x = (const bf16*)d_in[3];
    const bf16* B_mem0 = (const bf16*)d_in[4];
    const bf16* B_Wq = (const bf16*)d_in[5];
    const bf16* B_Wk = (const bf16*)d_in[6];
    const bf16* B_Wv = (const bf16*)d_in[7];
    const bf16* B_Wo = (const bf16*)d_in[8];
    bf16* out = (bf16*)d_out;

    static bool inited = false;
    static cudaStream_t s1, s2, s3, s4;
    static cudaEvent_t e_kv, e_s1, e_ch, e_q, e_s3, e_s4;
    if (!inited) {
        init_encode();
        cudaFuncSetAttribute(gemm_w_kernel, cudaFuncAttributeMaxDynamicSharedMemorySize, GW_SMEM);
        cudaFuncSetAttribute(gemm_s_kernel, cudaFuncAttributeMaxDynamicSharedMemorySize, GS_SMEM);
        cudaFuncSetAttribute(chain_kernel, cudaFuncAttributeMaxDynamicSharedMemorySize, CH_SMEM);
        cudaFuncSetAttribute(chain_kernel, cudaFuncAttributeNonPortableClusterSizeAllowed, 1);
        cudaFuncSetAttribute(attn_a_kernel, cudaFuncAttributeMaxDynamicSharedMemorySize, AA_SMEM);
        cudaFuncSetAttribute(attn_b_kernel, cudaFuncAttributeMaxDynamicSharedMemorySize, AB_SMEM);
        int plo = 0, phi = 0;
        cudaDeviceGetStreamPriorityRange(&plo, &phi);
        cudaStreamCreateWithPriority(&s1, cudaStreamNonBlocking, plo);
        cudaStreamCreateWithPriority(&s2, cudaStreamNonBlocking, phi);
        cudaStreamCreateWithPriority(&s3, cudaStreamNonBlocking, phi);
        cudaStreamCreateWithPriority(&s4, cudaStreamNonBlocking, phi);
        cudaEventCreateWithFlags(&e_kv, cudaEventDisableTiming);
        cudaEventCreateWithFlags(&e_s1, cudaEventDisableTiming);
        cudaEventCreateWithFlags(&e_ch, cudaEventDisableTiming);
        cudaEventCreateWithFlags(&e_q, cudaEventDisableTiming);
        cudaEventCreateWithFlags(&e_s3, cudaEventDisableTiming);
        cudaEventCreateWithFlags(&e_s4, cudaEventDisableTiming);
        inited = true;
    }
    void *qkvA, *oA, *qkvB, *kvmem, *oB, *part, *membuf, *flags;
    cudaGetSymbolAddress(&qkvA, g_qkvA); cudaGetSymbolAddress(&oA, g_oA); cudaGetSymbolAddress(&qkvB, g_qkvB);
    cudaGetSymbolAddress(&kvmem, g_kvmem); cudaGetSymbolAddress(&oB, g_oB); cudaGetSymbolAddress(&part, g_part);
    membuf = nullptr; cudaGetSymbolAddress(&flags, g_flags);
    cudaStream_t s0 = cudaStreamPerThread;

    cudaEventRecord(e_kv, s0);
    cudaStreamWaitEvent(s1, e_kv, 0);
    cudaStreamWaitEvent(s2, e_kv, 0);
    ChainParams pc;
    pc.tmW[0] = make_tmap_3d64(B_Wq, 512, 4096, 4096, 256, 1);
    pc.tmW[1] = make_tmap_3d64(B_Wk, 512, 4096, 4096, 256, 1);
    pc.tmW[2] = make_tmap_3d64(B_Wv, 512, 4096, 4096, 256, 1);
    pc.tmWo = make_tmap_3d64(B_Wo, 4096, 512, 512, 128, 1);
    pc.tmKV = make_tmap_3d64(qkvB, 2048, 12288, 12288, 32, 1);
    pc.mem0 = B_mem0; pc.kvmem = (bf16*)kvmem; pc.part = (float*)part; pc.membuf = (uint4*)membuf;
    pc.flags = (const unsigned int*)flags; pc.flag_target = 128; pc.dbg = nullptr; pc.seg_flags = (unsigned int*)flags + 1024;
    {
        cudaLaunchConfig_t cfg = {};
        cfg.gridDim = dim3(64); cfg.blockDim = dim3(384); cfg.dynamicSmemBytes = CH_SMEM; cfg.stream = s2;
        cudaLaunchAttribute at[2];
        at[0].id = cudaLaunchAttributeClusterDimension; at[0].val.clusterDim.x = 16; at[0].val.clusterDim.y = 1; at[0].val.clusterDim.z = 1;
        cfg.attrs = at; cfg.numAttrs = 1;
        cudaLaunchKernelEx(&cfg, chain_kernel, pc);
    }

    cudaEventRecord(e_ch, s2);
    delay_kernel<<<1, 32, 0, s1>>>();
    GemmWParams pkv;
    pkv.tmA = make_tmap_3d64(B_x, 2048, 512, 512, 128, 1);
    pkv.tmB[0] = make_tmap_3d64(B_Wk, 512, 4096, 4096, 64, 2);
    pkv.tmB[1] = make_tmap_3d64(B_Wv, 512, 4096, 4096, 64, 2);
    pkv.tmB[2] = make_tmap_3d64(B_Wq, 512, 4096, 4096, 64, 2);
    pkv.tmC = make_tmap_3d64(qkvB, 2048, 12288, 12288, 128, 1);
    pkv.ntiles_per_mat = 32; pkv.c_col64[0] = 64; pkv.c_col64[1] = 128; pkv.c_col64[2] = 0;
    pkv.m_splits = 1; pkv.mtiles_per_cta = 16; pkv.flag_mats = 2; pkv.flags = (unsigned int*)flags; pkv.tl_id = 1;
    gemm_w_kernel<<<64, 384, GW_SMEM, s1>>>(pkv);

    GemmWParams pq = pkv;
    pq.tmB[0] = pkv.tmB[2]; pq.c_col64[0] = 0; pq.m_splits = 2; pq.mtiles_per_cta = 8; pq.flag_mats = 0; pq.flags = nullptr; pq.tl_id = 2;
    gemm_w_kernel<<<64, 384, GW_SMEM, s1>>>(pq);
    cudaEventRecord(e_q, s1);
    cudaStreamWaitEvent(s3, e_q, 0);
    cudaStreamWaitEvent(s4, e_q, 0);
    AttnBParams pb;
    pb.tmQKV = make_tmap_3d64(qkvB, 2048, 12288, 12288, 32, 1);
    pb.tmKVM = make_tmap_3d64(kvmem, 512, 8192, 8192, 8, 1);
    pb.tmO = make_tmap_3d64(oB, 2048, 4096, 4096, 32, 1);
    pb.seg_flags = (const unsigned int*)flags + 1024; pb.seg_target = 64; pb.tile_flags = (unsigned int*)flags + 64;
    attn_b_kernel<<<AB_GRID, 128, AB_SMEM, s3>>>(pb);
    cudaEventRecord(e_s3, s3);

    GemmSParams p4;
    p4.tmA = make_tmap_3d64(oB, 2048, 4096, 4096, 128, 1);
    p4.tmB = make_tmap_3d64(B_Wo, 4096, 512, 512, 64, 2);
    p4.tmC = make_tmap_3d64(out, 2048, 1024, 1024, 64, 1);
    p4.n_tiles = 4; p4.m_tiles = 16; p4.c = out; p4.ldc = 1024; p4.kblocks_half = 32; p4.c_col64 = 8;
    p4.tile_flags = (const unsigned int*)flags + 64; p4.tile_target = 128;
    {
        cudaLaunchConfig_t cfg = {};
        cfg.gridDim = dim3(G4_GRID); cfg.blockDim = dim3(288); cfg.dynamicSmemBytes = GS_SMEM; cfg.stream = s4;
        cudaLaunchAttribute at[2];
        at[0].id = cudaLaunchAttributeClusterDimension; at[0].val.clusterDim.x = 2; at[0].val.clusterDim.y = 1; at[0].val.clusterDim.z = 1;
        cfg.attrs = at; cfg.numAttrs = 1;
        cudaLaunchKernelEx(&cfg, gemm_s_kernel, p4);
    }
    cudaEventRecord(e_s4, s4);

    GemmWParams p1;
    p1.tmA = make_tmap_3d64(A_x, 2048, 512, 512, 128, 1);
    p1.tmB[0] = make_tmap_3d64(A_wqkv, 512, 1536, 1536, 64, 2); p1.tmB[1] = p1.tmB[0]; p1.tmB[2] = p1.tmB[0];
    p1.tmC = make_tmap_3d64(qkvA, 2048, 1536, 1536, 128, 1);
    p1.ntiles_per_mat = 12; p1.c_col64[0] = p1.c_col64[1] = p1.c_col64[2] = 0;
    p1.m_splits = 4; p1.mtiles_per_cta = 4; p1.flag_mats = 0; p1.flags = nullptr; p1.tl_id = 3;
    gemm_w_kernel<<<48, 384, GW_SMEM, s1>>>(p1);

    AttnAParams pa;
    {
        cuuint64_t dims[2] = {1536, 2048}; cuuint64_t strides[1] = {3072}; cuuint32_t box[2] = {16, AA_KT}; cuuint32_t es[2] = {1, 1};
        g_encode(&pa.tmKV, CU_TENSOR_MAP_DATA_TYPE_BFLOAT16, 2, qkvA, dims, strides, box, es, CU_TENSOR_MAP_INTERLEAVE_NONE,
                 CU_TENSOR_MAP_SWIZZLE_32B, CU_TENSOR_MAP_L2_PROMOTION_L2_128B, CU_TENSOR_MAP_FLOAT_OOB_FILL_NONE);
    }
    pa.qkv = (const bf16*)qkvA; pa.o = (bf16*)oA;
    attn_a_kernel<<<256, 256, AA_SMEM, s1>>>(pa);

    GemmWParams p2;
    p2.tmA = make_tmap_3d64(oA, 2048, 512, 512, 128, 1);
    p2.tmB[0] = make_tmap_3d64(A_wo, 512, 512, 512, 64, 2); p2.tmB[1] = p2.tmB[0]; p2.tmB[2] = p2.tmB[0];
    p2.tmC = make_tmap_3d64(out, 2048, 1024, 1024, 128, 1);
    p2.ntiles_per_mat = 4; p2.c_col64[0] = p2.c_col64[1] = p2.c_col64[2] = 0;
    p2.m_splits = 16; p2.mtiles_per_cta = 1; p2.flag_mats = 0; p2.flags = nullptr; p2.tl_id = 5;
    gemm_w_kernel<<<64, 384, GW_SMEM, s1>>>(p2);

    cudaEventRecord(e_s1, s1);
    cudaStreamWaitEvent(s0, e_s1, 0);
    cudaStreamWaitEvent(s0, e_ch, 0);
    cudaStreamWaitEvent(s0, e_s3, 0);
    cudaStreamWaitEvent(s0, e_s4, 0);
    cleanup_kernel<<<64, 256, 0, s0>>>();
}
```

```cpp
#include <cuda_runtime.h>
#include <cuda_bf16.h>
#include <cuda.h>
#include <stdint.h>

typedef __nv_bfloat16 bf16;

__device__ __forceinline__ uint32_t smem_u32(const void* p) { return (uint32_t)__cvta_generic_to_shared(p); }
__device__ __forceinline__ void mbar_init(uint32_t bar, uint32_t cnt) {
    asm volatile("mbarrier.init.shared::cta.b64 [%0], %1;" :: "r"(bar), "r"(cnt) : "memory");
}
__device__ __forceinline__ void mbar_expect_tx(uint32_t bar, uint32_t bytes) {
    asm volatile("mbarrier.arrive.expect_tx.shared::cta.b64 _, [%0], %1;" :: "r"(bar), "r"(bytes) : "memory");
}
__device__ __forceinline__ void mbar_arrive(uint32_t bar) {
    asm volatile("mbarrier.arrive.shared::cta.b64 _, [%0];" :: "r"(bar) : "memory");
}
__device__ __forceinline__ bool mbar_try_wait(uint32_t bar, uint32_t parity) {
    uint32_t ok;
    asm volatile("{\n.reg .pred p;\nmbarrier.try_wait.parity.shared::cta.b64 p, [%1], %2;\nselp.u32 %0, 1, 0, p;\n}"
                 : "=r"(ok) : "r"(bar), "r"(parity) : "memory");
    return ok != 0;
}
__device__ __forceinline__ void mbar_wait(uint32_t bar, uint32_t parity) {
    uint32_t n = 0;
    while (!mbar_try_wait(bar, parity)) { if (++n > (1u << 20)) break; }
}
__device__ __forceinline__ void fence_proxy_async_smem() { asm volatile("fence.proxy.async.shared::cta;" ::: "memory"); }
__device__ __forceinline__ void fence_proxy_async_all() { asm volatile("fence.proxy.async;" ::: "memory"); }
__device__ __forceinline__ void fence_mbar_init() { asm volatile("fence.mbarrier_init.release.cluster;" ::: "memory"); }

__device__ __forceinline__ void tma_load_3d(uint32_t dst, const CUtensorMap* tm, int c0, int c1, int c2, uint32_t bar) {
    asm volatile("cp.async.bulk.tensor.3d.shared::cluster.global.mbarrier::complete_tx::bytes [%0], [%1, {%3, %4, %5}], [%2];"
                 :: "r"(dst), "l"(tm), "r"(bar), "r"(c0), "r"(c1), "r"(c2) : "memory");
}
__device__ __forceinline__ void tma_load_2d(uint32_t dst, const CUtensorMap* tm, int c0, int c1, uint32_t bar) {
    asm volatile("cp.async.bulk.tensor.2d.shared::cluster.global.mbarrier::complete_tx::bytes [%0], [%1, {%3, %4}], [%2];"
                 :: "r"(dst), "l"(tm), "r"(bar), "r"(c0), "r"(c1) : "memory");
}
__device__ __forceinline__ void tma_store_3d(const CUtensorMap* tm, uint32_t src, int c0, int c1, int c2) {
    asm volatile("cp.async.bulk.tensor.3d.global.shared::cta.bulk_group [%0, {%2, %3, %4}], [%1];"
                 :: "l"(tm), "r"(src), "r"(c0), "r"(c1), "r"(c2) : "memory");
}
__device__ __forceinline__ void bulk_commit() { asm volatile("cp.async.bulk.commit_group;" ::: "memory"); }
__device__ __forceinline__ void bulk_wait_read0() { asm volatile("cp.async.bulk.wait_group.read 0;" ::: "memory"); }
__device__ __forceinline__ void bulk_wait_all0() { asm volatile("cp.async.bulk.wait_group 0;" ::: "memory"); }
__device__ __forceinline__ void prefetch_tmap(const CUtensorMap* tm) {
    asm volatile("prefetch.tensormap [%0];" :: "l"(tm) : "memory");
}

__device__ __forceinline__ void wg_fence() { asm volatile("wgmma.fence.sync.aligned;" ::: "memory"); }
__device__ __forceinline__ void wg_commit() { asm volatile("wgmma.commit_group.sync.aligned;" ::: "memory"); }
template <int N> __device__ __forceinline__ void wg_wait() { asm volatile("wgmma.wait_group.sync.aligned %0;" :: "n"(N) : "memory"); }

__device__ __forceinline__ void named_bar_sync(int id, int nthreads) {
    asm volatile("bar.sync %0, %1;" :: "r"(id), "r"(nthreads) : "memory");
}
__device__ __forceinline__ void named_bar_arrive(int id, int nthreads) {
    asm volatile("bar.arrive %0, %1;" :: "r"(id), "r"(nthreads) : "memory");
}

__device__ __forceinline__ uint64_t make_desc(uint32_t saddr, uint32_t lbo_bytes, uint32_t sbo_bytes) {
    return (uint64_t)((saddr & 0x3FFFF) >> 4) | ((uint64_t)(lbo_bytes >> 4) << 16) | ((uint64_t)(sbo_bytes >> 4) << 32) | ((uint64_t)1 << 62);
}

__device__ __forceinline__ uint32_t pack_bf16(float lo, float hi) {
    uint32_t r;
    asm("cvt.rn.bf16x2.f32 %0, %1, %2;" : "=r"(r) : "f"(hi), "f"(lo));
    return r;
}
__device__ __forceinline__ void stmatrix_x4(uint32_t addr, uint32_t r0, uint32_t r1, uint32_t r2, uint32_t r3) {
    asm volatile("stmatrix.sync.aligned.m8n8.x4.shared.b16 [%0], {%1,%2,%3,%4};" :: "r"(addr), "r"(r0), "r"(r1), "r"(r2), "r"(r3) : "memory");
}
__device__ __forceinline__ void ldmatrix_x4(uint32_t& r0, uint32_t& r1, uint32_t& r2, uint32_t& r3, uint32_t addr) {
    asm volatile("ldmatrix.sync.aligned.m8n8.x4.shared.b16 {%0,%1,%2,%3}, [%4];" : "=r"(r0), "=r"(r1), "=r"(r2), "=r"(r3) : "r"(addr) : "memory");
}
__device__ __forceinline__ void ldmatrix_x4_t(uint32_t& r0, uint32_t& r1, uint32_t& r2, uint32_t& r3, uint32_t addr) {
    asm volatile("ldmatrix.sync.aligned.m8n8.x4.trans.shared.b16 {%0,%1,%2,%3}, [%4];" : "=r"(r0), "=r"(r1), "=r"(r2), "=r"(r3) : "r"(addr) : "memory");
}
__device__ __forceinline__ void ldmatrix_x2(uint32_t& r0, uint32_t& r1, uint32_t addr) {
    asm volatile("ldmatrix.sync.aligned.m8n8.x2.shared.b16 {%0,%1}, [%2];" : "=r"(r0), "=r"(r1) : "r"(addr) : "memory");
}
__device__ __forceinline__ void ldmatrix_x2_t(uint32_t& r0, uint32_t& r1, uint32_t addr) {
    asm volatile("ldmatrix.sync.aligned.m8n8.x2.trans.shared.b16 {%0,%1}, [%2];" : "=r"(r0), "=r"(r1) : "r"(addr) : "memory");
}
__device__ __forceinline__ void mma16816(float* c, const uint32_t* a, uint32_t b0, uint32_t b1) {
    asm volatile("mma.sync.aligned.m16n8k16.row.col.f32.bf16.bf16.f32 {%0,%1,%2,%3}, {%4,%5,%6,%7}, {%8,%9}, {%0,%1,%2,%3};"
                 : "+f"(c[0]), "+f"(c[1]), "+f"(c[2]), "+f"(c[3]) : "r"(a[0]), "r"(a[1]), "r"(a[2]), "r"(a[3]), "r"(b0), "r"(b1));
}

__device__ __forceinline__ void wgmma_m64n128k16_ss_tb(float* d, uint64_t da, uint64_t db, int scale_d) {
    asm volatile(
        "{\n.reg .pred p;\nsetp.ne.b32 p, %66, 0;\n"
        "wgmma.mma_async.sync.aligned.m64n128k16.f32.bf16.bf16 "
        "{%0,%1,%2,%3,%4,%5,%6,%7,%8,%9,%10,%11,%12,%13,%14,%15,"
        "%16,%17,%18,%19,%20,%21,%22,%23,%24,%25,%26,%27,%28,%29,%30,%31,"
        "%32,%33,%34,%35,%36,%37,%38,%39,%40,%41,%42,%43,%44,%45,%46,%47,"
        "%48,%49,%50,%51,%52,%53,%54,%55,%56,%57,%58,%59,%60,%61,%62,%63},"
        " %64, %65, p, 1, 1, 0, 1;\n}\n"
        : "+f"(d[0]), "+f"(d[1]), "+f"(d[2]), "+f"(d[3]), "+f"(d[4]), "+f"(d[5]), "+f"(d[6]), "+f"(d[7]),
          "+f"(d[8]), "+f"(d[9]), "+f"(d[10]), "+f"(d[11]), "+f"(d[12]), "+f"(d[13]), "+f"(d[14]), "+f"(d[15]),
          "+f"(d[16]), "+f"(d[17]), "+f"(d[18]), "+f"(d[19]), "+f"(d[20]), "+f"(d[21]), "+f"(d[22]), "+f"(d[23]),
          "+f"(d[24]), "+f"(d[25]), "+f"(d[26]), "+f"(d[27]), "+f"(d[28]), "+f"(d[29]), "+f"(d[30]), "+f"(d[31]),
          "+f"(d[32]), "+f"(d[33]), "+f"(d[34]), "+f"(d[35]), "+f"(d[36]), "+f"(d[37]), "+f"(d[38]), "+f"(d[39]),
          "+f"(d[40]), "+f"(d[41]), "+f"(d[42]), "+f"(d[43]), "+f"(d[44]), "+f"(d[45]), "+f"(d[46]), "+f"(d[47]),
          "+f"(d[48]), "+f"(d[49]), "+f"(d[50]), "+f"(d[51]), "+f"(d[52]), "+f"(d[53]), "+f"(d[54]), "+f"(d[55]),
          "+f"(d[56]), "+f"(d[57]), "+f"(d[58]), "+f"(d[59]), "+f"(d[60]), "+f"(d[61]), "+f"(d[62]), "+f"(d[63])
        : "l"(da), "l"(db), "r"(scale_d));
}

__device__ __forceinline__ void wgmma_m64n128k16_rs(float* d, const uint32_t* a, uint64_t db, int scale_d) {
    asm volatile(
        "{\n.reg .pred p;\nsetp.ne.b32 p, %69, 0;\n"
        "wgmma.mma_async.sync.aligned.m64n128k16.f32.bf16.bf16 "
        "{%0,%1,%2,%3,%4,%5,%6,%7,%8,%9,%10,%11,%12,%13,%14,%15,"
        "%16,%17,%18,%19,%20,%21,%22,%23,%24,%25,%26,%27,%28,%29,%30,%31,"
        "%32,%33,%34,%35,%36,%37,%38,%39,%40,%41,%42,%43,%44,%45,%46,%47,"
        "%48,%49,%50,%51,%52,%53,%54,%55,%56,%57,%58,%59,%60,%61,%62,%63},"
        " {%64,%65,%66,%67}, %68, p, 1, 1, 0;\n}\n"
        : "+f"(d[0]), "+f"(d[1]), "+f"(d[2]), "+f"(d[3]), "+f"(d[4]), "+f"(d[5]), "+f"(d[6]), "+f"(d[7]),
          "+f"(d[8]), "+f"(d[9]), "+f"(d[10]), "+f"(d[11]), "+f"(d[12]), "+f"(d[13]), "+f"(d[14]), "+f"(d[15]),
          "+f"(d[16]), "+f"(d[17]), "+f"(d[18]), "+f"(d[19]), "+f"(d[20]), "+f"(d[21]), "+f"(d[22]), "+f"(d[23]),
          "+f"(d[24]), "+f"(d[25]), "+f"(d[26]), "+f"(d[27]), "+f"(d[28]), "+f"(d[29]), "+f"(d[30]), "+f"(d[31]),
          "+f"(d[32]), "+f"(d[33]), "+f"(d[34]), "+f"(d[35]), "+f"(d[36]), "+f"(d[37]), "+f"(d[38]), "+f"(d[39]),
          "+f"(d[40]), "+f"(d[41]), "+f"(d[42]), "+f"(d[43]), "+f"(d[44]), "+f"(d[45]), "+f"(d[46]), "+f"(d[47]),
          "+f"(d[48]), "+f"(d[49]), "+f"(d[50]), "+f"(d[51]), "+f"(d[52]), "+f"(d[53]), "+f"(d[54]), "+f"(d[55]),
          "+f"(d[56]), "+f"(d[57]), "+f"(d[58]), "+f"(d[59]), "+f"(d[60]), "+f"(d[61]), "+f"(d[62]), "+f"(d[63])
        : "r"(a[0]), "r"(a[1]), "r"(a[2]), "r"(a[3]), "l"(db), "r"(scale_d));
}
__device__ __forceinline__ void stmatrix_x4_t(uint32_t addr, uint32_t r0, uint32_t r1, uint32_t r2, uint32_t r3) {
    asm volatile("stmatrix.sync.aligned.m8n8.x4.trans.shared.b16 [%0], {%1,%2,%3,%4};" :: "r"(addr), "r"(r0), "r"(r1), "r"(r2), "r"(r3) : "memory");
}
template <int R> __device__ __forceinline__ void reg_alloc() { asm volatile("setmaxnreg.inc.sync.aligned.u32 %0;" :: "n"(R)); }
template <int R> __device__ __forceinline__ void reg_dealloc() { asm volatile("setmaxnreg.dec.sync.aligned.u32 %0;" :: "n"(R)); }

#define TL_START(k)
#define TL_END(k)
struct GemmWParams {
    CUtensorMap tmA;
    CUtensorMap tmB[3];
    CUtensorMap tmC;
    int ntiles_per_mat;
    int c_col64[3];
    int m_splits;
    int mtiles_per_cta;
    int flag_mats;
    unsigned int* flags;
    int tl_id;
};

constexpr int GW_NST = 11;
constexpr int GW_SMEM = GW_NST * 16384 + 32768 + 256;

__global__ void __launch_bounds__(384, 1) gemm_w_kernel(const __grid_constant__ GemmWParams p) {
    extern __shared__ __align__(1024) unsigned char smem[];
    const uint32_t sA = smem_u32(smem);
    const uint32_t sOut = sA + GW_NST * 16384;
    const uint32_t bars = sOut + 32768;
    const uint32_t barFull = bars, barEmpty = bars + 8 * GW_NST, barStF = bars + 16 * GW_NST, barStE = barStF + 16;
    const int warp = __shfl_sync(0xffffffff, threadIdx.x >> 5, 0), lane = threadIdx.x & 31;
    TL_START(p.tl_id);
    const int gnt = blockIdx.x / p.m_splits;
    const int ms = blockIdx.x % p.m_splits;
    const int mat = gnt / p.ntiles_per_mat;
    const int nt = gnt % p.ntiles_per_mat;
    const int tile0 = ms * p.mtiles_per_cta;
    const int ntl = p.mtiles_per_cta;

    if (threadIdx.x == 0) {
        for (int i = 0; i < GW_NST; i++) { mbar_init(barFull + 8 * i, 1); mbar_init(barEmpty + 8 * i, 8); }
        for (int i = 0; i < 2; i++) { mbar_init(barStF + 8 * i, 4); mbar_init(barStE + 8 * i, 1); }
        fence_mbar_init();
    }
    __syncthreads();

    const int wgi = __shfl_sync(0xffffffff, threadIdx.x >> 7, 0);
    if (wgi == 0) {
        reg_dealloc<40>();
        if (warp == 0 && lane == 0) {
            const CUtensorMap* tmB = &p.tmB[mat];
            const int total = 8 + ntl * 8;
            for (int idx = 0; idx < total; idx++) {
                int slot = idx % GW_NST;
                if (idx >= GW_NST) mbar_wait(barEmpty + 8 * slot, ((idx / GW_NST) - 1) & 1);
                mbar_expect_tx(barFull + 8 * slot, 16384);
                if (idx < 8) tma_load_3d(sA + slot * 16384, tmB, 0, idx * 64, nt * 2, barFull + 8 * slot);
                else {
                    int t = (idx - 8) >> 3, j = (idx - 8) & 7;
                    tma_load_3d(sA + slot * 16384, &p.tmA, 0, (tile0 + t) * 128, j, barFull + 8 * slot);
                }
            }
        } else if ((warp == 1 || warp == 2) && lane == 0) {
            const int wg = warp - 1;
            const bool do_flag = (p.flags != nullptr) && (mat < p.flag_mats);
            for (int t = 0; t < ntl; t++) {
                mbar_wait(barStF + 8 * wg, t & 1);
                tma_store_3d(&p.tmC, sOut + wg * 16384, 0, (tile0 + t) * 128, p.c_col64[mat] + nt * 2 + wg);
                bulk_commit();
                bulk_wait_read0();
                mbar_arrive(barStE + 8 * wg);
                if (do_flag) {
                    bulk_wait_all0();
                    fence_proxy_async_all();
                    __threadfence();
                    atomicAdd(p.flags + tile0 + t, 1u);
                }
            }
            bulk_wait_all0();
        }
    } else {
        reg_alloc<232>();
        const int wg = (warp >> 2) - 1, wq = warp & 3;
        uint32_t w[32][4];
        float acc[64];
        {
            const int krow = (lane & 7) + ((lane >> 4) & 1) * 8;
            const int chunk = wq * 2 + ((lane >> 3) & 1);
#pragma unroll
            for (int kb = 0; kb < 8; kb++) {
                mbar_wait(barFull + 8 * kb, 0);
#pragma unroll
                for (int kk = 0; kk < 4; kk++) {
                    int r = kk * 16 + krow;
                    uint32_t addr = sA + kb * 16384 + wg * 8192 + r * 128 + ((chunk ^ (r & 7)) << 4);
                    ldmatrix_x4_t(w[kb * 4 + kk][0], w[kb * 4 + kk][1], w[kb * 4 + kk][2], w[kb * 4 + kk][3], addr);
                }
                __syncwarp();
                if (lane == 0) mbar_arrive(barEmpty + 8 * kb);
            }
        }
        int idx = 8;
        for (int t = 0; t < ntl; t++) {
            int prev_slot = 0;
            if (wg == 0) { if (t > 0) named_bar_sync(3, 256); }
            else named_bar_sync(4, 256);
#pragma unroll
            for (int j = 0; j < 8; j++, idx++) {
                int slot = idx % GW_NST;
                mbar_wait(barFull + 8 * slot, (idx / GW_NST) & 1);
                wg_fence();
                uint64_t db = make_desc(sA + slot * 16384, 16, 1024);
#pragma unroll
                for (int kk = 0; kk < 4; kk++)
                    wgmma_m64n128k16_rs(acc, w[j * 4 + kk], db + (uint64_t)(kk * 2), (j | kk) != 0);
                wg_commit();
                if (j == 7) {
                    if (wg == 0) named_bar_arrive(4, 256);
                    else if (t + 1 < ntl) named_bar_arrive(3, 256);
                }
                if (j > 0) {
                    wg_wait<1>();
                    if (lane == 0) mbar_arrive(barEmpty + 8 * prev_slot);
                }
                prev_slot = slot;
            }
            wg_wait<0>();
            if (lane == 0) mbar_arrive(barEmpty + 8 * prev_slot);
            if (t > 0) mbar_wait(barStE + 8 * wg, (t - 1) & 1);
            const uint32_t sbase = sOut + wg * 16384;
            const int mid = lane >> 3;
            const int chunk = wq * 2 + (mid & 1);
#pragma unroll
            for (int nb = 0; nb < 8; nb++) {
                const int a0 = nb * 8;
                uint32_t r0 = pack_bf16(acc[a0 + 0], acc[a0 + 1]);
                uint32_t r1 = pack_bf16(acc[a0 + 2], acc[a0 + 3]);
                uint32_t r2 = pack_bf16(acc[a0 + 4], acc[a0 + 5]);
                uint32_t r3 = pack_bf16(acc[a0 + 6], acc[a0 + 7]);
                int tok = nb * 16 + (mid >> 1) * 8 + (lane & 7);
                stmatrix_x4_t(sbase + tok * 128 + ((chunk ^ (tok & 7)) << 4), r0, r1, r2, r3);
            }
            fence_proxy_async_smem();
            __syncwarp();
            if (lane == 0) mbar_arrive(barStF + 8 * wg);
        }
    }
}

#define PACE 0
#define NSTEPS 64
#define POLL_B 1
#define POLL_R 1
struct ChainParams {
    CUtensorMap tmW[3];
    CUtensorMap tmWo;
    CUtensorMap tmKV;
    const bf16* mem0;
    bf16* kvmem;
    float* part;
    uint4* membuf;
    const unsigned int* flags;
    unsigned int flag_target;
    unsigned int* seg_flags;
    long long* dbg;
};

constexpr int CH_MEM_STRIDE = 1040;
constexpr int CH_Q_STRIDE = 144;
constexpr int CH_O_STRIDE = 272;
constexpr int CH_NKV = 4;
constexpr int CH_KV_BYTES = 15360;
constexpr int CH_OFF_WO = 0;
constexpr int CH_OFF_WV = 65536;
constexpr int CH_OFF_KV = 131072;
constexpr int CH_OFF_MEM = CH_OFF_KV + CH_NKV * CH_KV_BYTES;
constexpr int CH_OFF_RS = CH_OFF_MEM + 8192;
constexpr int CH_OFF_STG = CH_OFF_RS + 8192;
constexpr int CH_OFF_Q = CH_OFF_STG + 512;
constexpr int CH_OFF_O = CH_OFF_Q + 1152;
constexpr int CH_OFF_RED1 = CH_OFF_O + 2176;
constexpr int CH_OFF_SC = CH_OFF_RED1 + 6144;
constexpr int CH_OFF_RED2 = CH_OFF_SC + 1280;
constexpr int CH_OFF_ZERO = CH_OFF_RED2 + 2048;
constexpr int CH_OFF_BAR = CH_OFF_ZERO + 128;
constexpr int CH_OFF_TS = CH_OFF_BAR + 256;
constexpr int CH_SMEM = CH_OFF_TS + 1024;

__device__ __forceinline__ uint32_t mapa_u32(uint32_t addr, uint32_t rank) {
    uint32_t r; asm volatile("mapa.shared::cluster.u32 %0, %1, %2;" : "=r"(r) : "r"(addr), "r"(rank)); return r;
}
__device__ __forceinline__ void st_async_v4(uint32_t addr, uint32_t a, uint32_t b, uint32_t c, uint32_t d, uint32_t mbar) {
    asm volatile("st.async.shared::cluster.mbarrier::complete_tx::bytes.v4.b32 [%0], {%1,%2,%3,%4}, [%5];"
                 :: "r"(addr), "r"(a), "r"(b), "r"(c), "r"(d), "r"(mbar) : "memory");
}
__device__ __forceinline__ void st_async_v2(uint32_t addr, uint32_t a, uint32_t b, uint32_t mbar) {
    asm volatile("st.async.shared::cluster.mbarrier::complete_tx::bytes.v2.b32 [%0], {%1,%2}, [%3];"
                 :: "r"(addr), "r"(a), "r"(b), "r"(mbar) : "memory");
}
__device__ __forceinline__ bool mbar_try_wait_cl(uint32_t bar, uint32_t parity) {
    uint32_t ok;
    asm volatile("{\n.reg .pred p;\nmbarrier.try_wait.parity.acquire.cluster.shared::cta.b64 p, [%1], %2;\nselp.u32 %0, 1, 0, p;\n}"
                 : "=r"(ok) : "r"(bar), "r"(parity) : "memory");
    return ok != 0;
}
__device__ __forceinline__ void mbar_wait_cl(uint32_t bar, uint32_t parity) {
    uint32_t n = 0;
    while (!mbar_try_wait_cl(bar, parity)) { if (++n > (1u << 20)) break; }
}
__device__ __forceinline__ void cluster_sync_all() {
    asm volatile("barrier.cluster.arrive.aligned;\nbarrier.cluster.wait.aligned;" ::: "memory");
}
__device__ __forceinline__ uint4 ld_relaxed_v4(const void* p) {
    uint4 v;
    asm volatile("ld.relaxed.gpu.global.v4.u32 {%0,%1,%2,%3}, [%4];" : "=r"(v.x), "=r"(v.y), "=r"(v.z), "=r"(v.w) : "l"(p) : "memory");
    return v;
}
__device__ __forceinline__ void st_relaxed_v4(void* p, uint32_t a, uint32_t b, uint32_t c, uint32_t d) {
    asm volatile("st.relaxed.gpu.global.v4.u32 [%0], {%1,%2,%3,%4};" :: "l"(p), "r"(a), "r"(b), "r"(c), "r"(d) : "memory");
}
__device__ __forceinline__ unsigned int ld_acquire_u32(const unsigned int* p) {
    unsigned int v;
    asm volatile("ld.acquire.gpu.global.u32 %0, [%1];" : "=r"(v) : "l"(p) : "memory");
    return v;
}
__device__ __forceinline__ void lds128(uint32_t* r, uint32_t addr) {
    asm volatile("ld.shared.v4.u32 {%0,%1,%2,%3}, [%4];" : "=r"(r[0]), "=r"(r[1]), "=r"(r[2]), "=r"(r[3]) : "r"(addr) : "memory");
}
__device__ __forceinline__ float ex2_approx(float x) { float y; asm("ex2.approx.ftz.f32 %0, %1;" : "=f"(y) : "f"(x)); return y; }
__device__ __forceinline__ void mma_nv(float* c, const uint32_t* a, uint32_t b0, uint32_t b1) {
    asm("mma.sync.aligned.m16n8k16.row.col.f32.bf16.bf16.f32 {%0,%1,%2,%3}, {%4,%5,%6,%7}, {%8,%9}, {%0,%1,%2,%3};"
        : "+f"(c[0]), "+f"(c[1]), "+f"(c[2]), "+f"(c[3]) : "r"(a[0]), "r"(a[1]), "r"(a[2]), "r"(a[3]), "r"(b0), "r"(b1));
}

__device__ __forceinline__ void st_relaxed_v2(void* p, uint32_t a, uint32_t b) {
    asm volatile("st.relaxed.gpu.global.v2.u32 [%0], {%1,%2};" :: "l"(p), "r"(a), "r"(b) : "memory");
}

#define TSX(i)
__global__ void __launch_bounds__(384, 1) chain_kernel(const __grid_constant__ ChainParams p) {
    extern __shared__ __align__(1024) unsigned char smem[];
    const uint32_t sb = smem_u32(smem);
    int tid; asm volatile("mov.u32 %0, %%tid.x;" : "=r"(tid));
    int bid; asm volatile("mov.u32 %0, %%ctaid.x;" : "=r"(bid));
    const int lane = tid & 31;
    const int warp = __shfl_sync(0xffffffff, tid >> 5, 0);
    const int wgi = __shfl_sync(0xffffffff, tid >> 7, 0);
    const int rank = bid & 15, cl = bid >> 4;
    const int head = bid >> 1, half = bid & 1;
    TL_START(0);
    const uint32_t barSc = sb + CH_OFF_BAR, barV = barSc + 8, barLd = barSc + 16, barKV = barSc + 24, barMem = barKV + 8 * CH_NKV, barRS = barMem + 8;

    if (tid == 0) {
        mbar_init(barSc, 1); mbar_init(barV, 1); mbar_init(barLd, 1); mbar_init(barMem, 1); mbar_init(barRS, 1);
        for (int i = 0; i < CH_NKV; i++) mbar_init(barKV + 8 * i, 1);
        fence_mbar_init();
        mbar_expect_tx(barSc, 1280);
        mbar_expect_tx(barV, 1024);
        mbar_expect_tx(barMem, 8192);
        mbar_expect_tx(barRS, 4096);
    }
    if (tid < 32) *reinterpret_cast<uint32_t*>(smem + CH_OFF_ZERO + tid * 4) = 0u;
    __syncthreads();
    cluster_sync_all();
    const uint32_t peer = rank ^ 1;
    const int t4 = lane & 3, g8 = lane >> 2;
    const int lr = lane & 7, lm = lane >> 3;

    if (wgi < 2) {
        reg_alloc<208>();
        const int g = warp >> 1, kh = warp & 1;
        uint32_t wqk[2][16][4];
        {
            const int c64 = head * 2 + half;
            const int krow = lr + ((lane >> 4) & 1) * 8;
            const int chunk = g * 2 + (lm & 1);
            if (tid == 0) {
                mbar_expect_tx(barLd, 131072);
                tma_load_3d(sb + CH_OFF_WO, &p.tmW[0], 0, 0, c64, barLd);
                tma_load_3d(sb + CH_OFF_WO + 32768, &p.tmW[0], 0, 256, c64, barLd);
                tma_load_3d(sb + CH_OFF_WV, &p.tmW[1], 0, 0, c64, barLd);
                tma_load_3d(sb + CH_OFF_WV + 32768, &p.tmW[1], 0, 256, c64, barLd);
            }
            mbar_wait(barLd, 0);
#pragma unroll
            for (int m = 0; m < 2; m++)
#pragma unroll
                for (int ks = 0; ks < 16; ks++) {
                    int r = kh * 256 + ks * 16 + krow;
                    uint32_t addr = sb + (m == 0 ? CH_OFF_WO : CH_OFF_WV) + r * 128 + ((chunk ^ (r & 7)) << 4);
                    ldmatrix_x4_t(wqk[m][ks][0], wqk[m][ks][1], wqk[m][ks][2], wqk[m][ks][3], addr);
                }
            named_bar_sync(7, 256);
            if (tid == 0) {
                mbar_expect_tx(barLd, 131072);
                tma_load_3d(sb + CH_OFF_WV, &p.tmW[2], 0, 0, c64, barLd);
                tma_load_3d(sb + CH_OFF_WV + 32768, &p.tmW[2], 0, 256, c64, barLd);
                for (int i = 0; i < 4; i++) tma_load_3d(sb + CH_OFF_WO + i * 16384, &p.tmWo, 0, head * 128, half * 4 + i, barLd);
            }
            mbar_wait(barLd, 1);
            uint32_t f[16][4];
#pragma unroll
            for (int ks = 0; ks < 16; ks++) {
                int r = kh * 256 + ks * 16 + krow;
                ldmatrix_x4_t(f[ks][0], f[ks][1], f[ks][2], f[ks][3], sb + CH_OFF_WV + r * 128 + ((chunk ^ (r & 7)) << 4));
            }
            named_bar_sync(7, 256);
#pragma unroll
            for (int ks = 0; ks < 16; ks++)
                asm volatile("st.shared.v4.u32 [%0], {%1,%2,%3,%4};" :: "r"(sb + CH_OFF_WV + ((warp * 16 + ks) * 32 + lane) * 16), "r"(f[ks][0]), "r"(f[ks][1]), "r"(f[ks][2]), "r"(f[ks][3]) : "memory");
#pragma unroll
            for (int ks = 0; ks < 8; ks++)
#pragma unroll
                for (int mt = 0; mt < 2; mt++) {
                    int r = ks * 16 + krow;
                    int colchunk = warp * 4 + mt * 2 + (lm & 1);
                    ldmatrix_x4_t(f[ks * 2 + mt][0], f[ks * 2 + mt][1], f[ks * 2 + mt][2], f[ks * 2 + mt][3],
                                  sb + CH_OFF_WO + (colchunk >> 3) * 16384 + r * 128 + (((colchunk & 7) ^ (r & 7)) << 4));
                }
            named_bar_sync(7, 256);
#pragma unroll
            for (int i = 0; i < 16; i++)
                asm volatile("st.shared.v4.u32 [%0], {%1,%2,%3,%4};" :: "r"(sb + CH_OFF_WO + ((warp * 16 + i) * 32 + lane) * 16), "r"(f[i][0]), "r"(f[i][1]), "r"(f[i][2]), "r"(f[i][3]) : "memory");
            named_bar_sync(7, 256);
        }
        const uint32_t wvbase = sb + CH_OFF_WV + (warp * 16 * 32 + lane) * 16;
        const uint32_t wobase = sb + CH_OFF_WO + (warp * 16 * 32 + lane) * 16;
        const uint32_t bAddr = sb + CH_OFF_MEM + kh * 4096 + lr * 64 + ((lm ^ ((lr >> 1) & 3)) << 4);
        const uint32_t redMine = sb + CH_OFF_RED1 + warp * 512 + lane * 16, redOther = sb + CH_OFF_RED1 + (warp ^ 1) * 512 + lane * 16;
        const uint32_t redMineV = sb + CH_OFF_RED1 + 4096 + warp * 256 + lane * 8, redOtherV = sb + CH_OFF_RED1 + 4096 + (warp ^ 1) * 256 + lane * 8;
        const uint32_t qDst = sb + CH_OFF_Q + lr * CH_Q_STRIDE + (g * 16 + (lm & 1) * 8) * 2;
        const uint32_t kvOff = lr * 128 + (((g * 2 + (lm & 1)) ^ lr) << 4);
        const uint32_t peerBase = mapa_u32(sb, peer) - sb;
        const uint32_t oAddr = sb + CH_OFF_O + lr * CH_O_STRIDE + lm * 16;
        const uint32_t rsDst = mapa_u32(sb + CH_OFF_RS + (rank >> 1) * 512 + lane * 16, warp * 2 + half);
        const uint32_t rsBar = mapa_u32(barRS, warp * 2 + half);
        float* llW = p.part + ((size_t)(cl * 16 + rank) * 64 + tid) * 4;
        for (int s = 0; s < NSTEPS; s++) {
            const uint32_t sKV = sb + CH_OFF_KV + (s & (CH_NKV - 1)) * CH_KV_BYTES;
            uint32_t wo[16][4], wv[2][2][4];
#pragma unroll
            for (int i = 0; i < 8; i++) lds128(wo[i], wobase + i * 512);
            lds128(wv[0][0], wvbase); lds128(wv[0][1], wvbase + 512);
            TSX(0);
            if (s == 0) {
                for (int i = tid; i < 512; i += 256) {
                    int tok = i & 7, c = i >> 3;
                    uint4 v = *reinterpret_cast<const uint4*>(p.mem0 + tok * 512 + c * 8);
                    *reinterpret_cast<uint4*>(smem + CH_OFF_MEM + (c >> 2) * 512 + tok * 64 + (((c & 3) ^ ((tok >> 1) & 3)) << 4)) = v;
                }
                named_bar_sync(7, 256);
            } else {
                mbar_wait(barMem, (s - 1) & 1);
                if (tid == 0) mbar_expect_tx(barMem, 8192);
            }
            TSX(1);
            {
                float aq[4], ak[4], av[4];
#pragma unroll
                for (int i = 0; i < 4; i++) { aq[i] = ak[i] = av[i] = 0.f; }
                uint32_t b[2][4];
                ldmatrix_x4(b[0][0], b[0][1], b[0][2], b[0][3], bAddr);
#pragma unroll
                for (int kk = 0; kk < 8; kk++) {
                    if (kk + 1 < 8) {
                        ldmatrix_x4(b[(kk + 1) & 1][0], b[(kk + 1) & 1][1], b[(kk + 1) & 1][2], b[(kk + 1) & 1][3], bAddr + (kk + 1) * 512);
                        lds128(wv[(kk + 1) & 1][0], wvbase + (2 * kk + 2) * 512);
                        lds128(wv[(kk + 1) & 1][1], wvbase + (2 * kk + 3) * 512);
                    }
                    mma_nv(aq, wqk[0][2 * kk], b[kk & 1][0], b[kk & 1][1]);
                    mma_nv(ak, wqk[1][2 * kk], b[kk & 1][0], b[kk & 1][1]);
                    mma_nv(av, wv[kk & 1][0], b[kk & 1][0], b[kk & 1][1]);
                    mma_nv(aq, wqk[0][2 * kk + 1], b[kk & 1][2], b[kk & 1][3]);
                    mma_nv(ak, wqk[1][2 * kk + 1], b[kk & 1][2], b[kk & 1][3]);
                    mma_nv(av, wv[kk & 1][1], b[kk & 1][2], b[kk & 1][3]);
                }
                TSX(2);
                float gv[6], kp[6];
#pragma unroll
                for (int i = 0; i < 4; i++) {
                    gv[i] = kh == 0 ? ak[i] : aq[i];
                    kp[i] = kh == 0 ? aq[i] : ak[i];
                }
                gv[4] = kh == 0 ? av[2] : av[0]; gv[5] = kh == 0 ? av[3] : av[1];
                kp[4] = kh == 0 ? av[0] : av[2]; kp[5] = kh == 0 ? av[1] : av[3];
                asm volatile("st.shared.v4.f32 [%0], {%1,%2,%3,%4};" :: "r"(redMine), "f"(gv[0]), "f"(gv[1]), "f"(gv[2]), "f"(gv[3]) : "memory");
                asm volatile("st.shared.v2.f32 [%0], {%1,%2};" :: "r"(redMineV), "f"(gv[4]), "f"(gv[5]) : "memory");
                named_bar_sync(1 + g, 64);
                float o0, o1, o2, o3, o4, o5;
                asm volatile("ld.shared.v4.f32 {%0,%1,%2,%3}, [%4];" : "=f"(o0), "=f"(o1), "=f"(o2), "=f"(o3) : "r"(redOther) : "memory");
                asm volatile("ld.shared.v2.f32 {%0,%1}, [%2];" : "=f"(o4), "=f"(o5) : "r"(redOtherV) : "memory");
                uint32_t r0 = pack_bf16(kp[0] + o0, kp[1] + o1);
                uint32_t r1 = pack_bf16(kp[2] + o2, kp[3] + o3);
                uint32_t r2 = pack_bf16(kp[4] + o4, kp[5] + o5);
                asm volatile("stmatrix.sync.aligned.m8n8.x2.trans.shared.b16 [%0], {%1,%2};" :: "r"(kh == 0 ? qDst : sKV + kvOff), "r"(r0), "r"(r1) : "memory");
                const uint32_t vAddr = sKV + 5120 + half * 5120 + lr * 128 + (((g * 2 + kh) ^ lr) << 4);
                asm volatile("stmatrix.sync.aligned.m8n8.x1.trans.shared.b16 [%0], {%1};" :: "r"(vAddr), "r"(r2) : "memory");
                named_bar_arrive(5, 384);
                TSX(3);
                __syncwarp();
                if (lane < 8) {
                    uint32_t f[4];
                    lds128(f, vAddr);
                    st_async_v4(vAddr + peerBase, f[0], f[1], f[2], f[3], barV + peerBase);
                }
            }
            if (s == NSTEPS - 1) break;
            named_bar_sync(10, 384);
#pragma unroll
            for (int i = 8; i < 16; i++) {
                lds128(wo[i], wobase + i * 512);
            }
            TSX(4);
            named_bar_sync(8, 384);
            TSX(5);
            const uint32_t tag = ((s >> 1) + 1) & 1;
            const uint32_t slotOff = (s & 1) * (64 * 256);
            {
                float a2[2][2][4];
#pragma unroll
                for (int i = 0; i < 4; i++) { a2[0][0][i] = a2[0][1][i] = a2[1][0][i] = a2[1][1][i] = 0.f; }
                uint32_t b[4][4];
#pragma unroll
                for (int kk = 0; kk < 4; kk++) ldmatrix_x4(b[kk][0], b[kk][1], b[kk][2], b[kk][3], oAddr + kk * 64);
#pragma unroll
                for (int kk = 0; kk < 4; kk++) {
                    mma_nv(a2[0][0], wo[kk * 4 + 0], b[kk][0], b[kk][1]);
                    mma_nv(a2[1][0], wo[kk * 4 + 1], b[kk][0], b[kk][1]);
                    mma_nv(a2[0][1], wo[kk * 4 + 2], b[kk][2], b[kk][3]);
                    mma_nv(a2[1][1], wo[kk * 4 + 3], b[kk][2], b[kk][3]);
                }
                st_async_v4(rsDst, pack_bf16(a2[0][0][0] + a2[0][1][0], a2[0][0][1] + a2[0][1][1]), pack_bf16(a2[0][0][2] + a2[0][1][2], a2[0][0][3] + a2[0][1][3]),
                            pack_bf16(a2[1][0][0] + a2[1][1][0], a2[1][0][1] + a2[1][1][1]), pack_bf16(a2[1][0][2] + a2[1][1][2], a2[1][0][3] + a2[1][1][3]), rsBar);
            }
            TSX(6);
            if (warp < 2) {
                mbar_wait(barRS, s & 1);
                TSX(7);
                uint32_t u[8][2];
#pragma unroll
                for (int h = 0; h < 8; h++)
                    asm volatile("ld.shared.v2.u32 {%0,%1}, [%2];" : "=r"(u[h][0]), "=r"(u[h][1]) : "r"(sb + CH_OFF_RS + h * 512 + lane * 16 + warp * 8) : "memory");
                if (tid == 0) mbar_expect_tx(barRS, 4096);
                float f0 = 0.f, f1 = 0.f, f2 = 0.f, f3 = 0.f;
                {
                    float a[8], b[8], c[8], d[8];
#pragma unroll
                    for (int h = 0; h < 8; h++) {
                        a[h] = __uint_as_float(u[h][0] << 16); b[h] = __uint_as_float(u[h][0] & 0xffff0000u);
                        c[h] = __uint_as_float(u[h][1] << 16); d[h] = __uint_as_float(u[h][1] & 0xffff0000u);
                    }
                    f0 = ((a[0] + a[1]) + (a[2] + a[3])) + ((a[4] + a[5]) + (a[6] + a[7]));
                    f1 = ((b[0] + b[1]) + (b[2] + b[3])) + ((b[4] + b[5]) + (b[6] + b[7]));
                    f2 = ((c[0] + c[1]) + (c[2] + c[3])) + ((c[4] + c[5]) + (c[6] + c[7]));
                    f3 = ((d[0] + d[1]) + (d[2] + d[3])) + ((d[4] + d[5]) + (d[6] + d[7]));
                }
                const uint32_t x0 = (__float_as_uint(f0) & ~1u) | tag;
                st_relaxed_v4(llW + slotOff, x0, __float_as_uint(f1), __float_as_uint(f2), __float_as_uint(f3));
                const float* r1 = p.part + slotOff + ((size_t)((cl ^ 1) * 16 + rank) * 64 + tid) * 4;
                const float* r2 = p.part + slotOff + ((size_t)((cl ^ 2) * 16 + rank) * 64 + tid) * 4;
                const float* r3 = p.part + slotOff + ((size_t)((cl ^ 3) * 16 + rank) * 64 + tid) * 4;
                uint4 v1, v2, v3;
                uint32_t n = 0;
                do { v1 = ld_relaxed_v4(r1); v2 = ld_relaxed_v4(r2); v3 = ld_relaxed_v4(r3); }
                while (POLL_R && (((v1.x ^ tag) | (v2.x ^ tag) | (v3.x ^ tag)) & 1u) && ++n < (1u << 22));
                TSX(8);
                f0 = (__uint_as_float(x0) + __uint_as_float(v1.x)) + (__uint_as_float(v2.x) + __uint_as_float(v3.x));
                f1 = (f1 + __uint_as_float(v1.y)) + (__uint_as_float(v2.y) + __uint_as_float(v3.y));
                f2 = (f2 + __uint_as_float(v1.z)) + (__uint_as_float(v2.z) + __uint_as_float(v3.z));
                f3 = (f3 + __uint_as_float(v1.w)) + (__uint_as_float(v2.w) + __uint_as_float(v3.w));
                const int ch = warp * 2 + (lm & 1);
                asm volatile("stmatrix.sync.aligned.m8n8.x2.trans.shared.b16 [%0], {%1,%2};"
                             :: "r"(sb + CH_OFF_STG + lr * 64 + ((ch ^ ((lr >> 1) & 3)) << 4)), "r"(pack_bf16(f0, f1)), "r"(pack_bf16(f2, f3)) : "memory");
                named_bar_sync(9, 64);
                uint32_t f[4];
                lds128(f, sb + CH_OFF_STG + lane * 16);
                const uint32_t dst0 = sb + CH_OFF_MEM + (half * 8 + (rank >> 1)) * 512 + lane * 16;
#pragma unroll
                for (int d = 0; d < 8; d++) {
                    const uint32_t dr = warp * 8 + d;
                    st_async_v4(mapa_u32(dst0, dr), f[0], f[1], f[2], f[3], mapa_u32(barMem, dr));
                }
                TSX(9);
            }
        }
    } else {
        reg_dealloc<88>();
        const int aw = warp - 8;
        const uint32_t peerBase = mapa_u32(sb, peer) - sb;
        const float sm_scale = 0.08838834764831845f * 1.4426950408889634f;
        const int kc64 = 64 + head * 2 + half, vc64 = 128 + head * 2;
        auto issue_kv = [&](int s) {
            if ((s & 3) == 0) {
                uint32_t n = 0;
                while (ld_acquire_u32(p.flags + (s >> 2)) < p.flag_target) { if (++n > (1u << 22)) break; }
                fence_proxy_async_all();
            }
            int st = s & (CH_NKV - 1);
            uint32_t base = sb + CH_OFF_KV + st * CH_KV_BYTES;
            mbar_expect_tx(barKV + 8 * st, 12288);
            tma_load_3d(base + 1024, &p.tmKV, 0, s * 32, kc64, barKV + 8 * st);
            tma_load_3d(base + 5120 + 1024, &p.tmKV, 0, s * 32, vc64, barKV + 8 * st);
            tma_load_3d(base + 10240 + 1024, &p.tmKV, 0, s * 32, vc64 + 1, barKV + 8 * st);
        };
        if (aw == 3 && lane == 0) { for (int s = 0; s < CH_NKV - 1; s++) issue_kv(s); }
        const uint32_t kOff0 = lr * 128 + ((lm ^ lr) << 4), kOff1 = lr * 128 + (((4 + lm) ^ lr) << 4);
        const uint32_t qAddr = (lm & 1) ? (sb + CH_OFF_ZERO) : (sb + CH_OFF_Q + lr * CH_Q_STRIDE + (lm >> 1) * 16);
        const uint32_t qStep = (lm & 1) ? 0u : 32u;
        const uint32_t vRow = ((lm >> 1) * 8 + lr) * 128;
        const uint32_t vOff0 = 5120 + (aw >> 1) * 5120 + vRow + ((((aw & 1) * 4 + (lm & 1)) ^ lr) << 4);
        const uint32_t vOff1 = 5120 + (aw >> 1) * 5120 + vRow + ((((aw & 1) * 4 + 2 + (lm & 1)) ^ lr) << 4);
        const uint32_t padAdj = (lm >> 1) ? 2048u : 0u;
        const uint32_t scAddr = sb + CH_OFF_SC + lane * 8;
        const uint32_t oDst = sb + CH_OFF_O + lr * CH_O_STRIDE + (aw * 32 + lm * 8) * 2;
        const int si = tid - 256, sw = si >> 6, stok = (si >> 3) & 7, scn = si & 7;
        const uint32_t kvmOff = (sw == 0 ? 0u : 5120u + half * 5120u) + stok * 128 + ((scn ^ stok) << 4);
        bf16* kvmDst = p.kvmem + (size_t)stok * 8192 + sw * 4096 + head * 128 + half * 64 + scn * 8;
        const bool leader = (tid == 256);
        for (int s = 0; s < NSTEPS; s++) {
            const uint32_t par = s & 1;
            const int st = s & (CH_NKV - 1);
            const uint32_t sKV = sb + CH_OFF_KV + st * CH_KV_BYTES;
            mbar_wait(barKV + 8 * st, (s / CH_NKV) & 1);
            uint32_t kb[2][4][4], va[3][2][4];
#pragma unroll
            for (int n = 0; n < 4; n++) {
                ldmatrix_x4(kb[0][n][0], kb[0][n][1], kb[0][n][2], kb[0][n][3], sKV + (n + 1) * 1024 + kOff0);
                ldmatrix_x4(kb[1][n][0], kb[1][n][1], kb[1][n][2], kb[1][n][3], sKV + (n + 1) * 1024 + kOff1);
            }
            TSX(0);
            named_bar_sync(5, 384);
            TSX(1);
            float sc[5][4];
#pragma unroll
            for (int n = 0; n < 5; n++) { sc[n][0] = sc[n][1] = sc[n][2] = sc[n][3] = 0.f; }
            {
                uint32_t a[4][4], km[2][4];
#pragma unroll
                for (int k = 0; k < 4; k++) ldmatrix_x4(a[k][0], a[k][1], a[k][2], a[k][3], qAddr + k * qStep);
                ldmatrix_x4(km[0][0], km[0][1], km[0][2], km[0][3], sKV + kOff0);
                ldmatrix_x4(km[1][0], km[1][1], km[1][2], km[1][3], sKV + kOff1);
#pragma unroll
                for (int kp = 0; kp < 2; kp++) {
#pragma unroll
                    for (int n = 0; n < 4; n++) mma_nv(sc[n + 1], a[kp * 2], kb[kp][n][0], kb[kp][n][1]);
#pragma unroll
                    for (int n = 0; n < 4; n++) mma_nv(sc[n + 1], a[kp * 2 + 1], kb[kp][n][2], kb[kp][n][3]);
                }
                mma_nv(sc[0], a[0], km[0][0], km[0][1]);
                mma_nv(sc[0], a[1], km[0][2], km[0][3]);
                mma_nv(sc[0], a[2], km[1][0], km[1][1]);
                mma_nv(sc[0], a[3], km[1][2], km[1][3]);
            }
            TSX(2);
            if (aw == 0) {
#pragma unroll
                for (int n = 0; n < 5; n++) st_async_v2(scAddr + peerBase + n * 256, __float_as_uint(sc[n][0]), __float_as_uint(sc[n][1]), barSc + peerBase);
            }
#pragma unroll
            for (int ks = 1; ks < 3; ks++) {
                const uint32_t adj = ks == 2 ? padAdj : 0u;
                ldmatrix_x4_t(va[ks][0][0], va[ks][0][1], va[ks][0][2], va[ks][0][3], sKV + ks * 2048 + vOff0 - adj);
                ldmatrix_x4_t(va[ks][1][0], va[ks][1][1], va[ks][1][2], va[ks][1][3], sKV + ks * 2048 + vOff1 - adj);
            }
            uint4 kvm;
            if (sw == 0) asm volatile("ld.shared.v4.u32 {%0,%1,%2,%3}, [%4];" : "=r"(kvm.x), "=r"(kvm.y), "=r"(kvm.z), "=r"(kvm.w) : "r"(sKV + kvmOff) : "memory");
            TSX(3);
            mbar_wait(barSc, par);
            TSX(4);
            float pp[5][2];
#pragma unroll
            for (int n = 0; n < 5; n++)
                asm volatile("ld.shared.v2.f32 {%0,%1}, [%2];" : "=f"(pp[n][0]), "=f"(pp[n][1]) : "r"(scAddr + n * 256) : "memory");
            if (leader) mbar_expect_tx(barSc, 1280);
#pragma unroll
            for (int n = 0; n < 5; n++) { sc[n][0] += pp[n][0]; sc[n][1] += pp[n][1]; }
            float mx = fmaxf(fmaxf(fmaxf(sc[0][0], sc[0][1]), fmaxf(sc[1][0], sc[1][1])), fmaxf(fmaxf(sc[2][0], sc[2][1]), fmaxf(sc[3][0], sc[3][1])));
            mx = fmaxf(mx, fmaxf(sc[4][0], sc[4][1]));
            mx = fmaxf(mx, __shfl_xor_sync(0xffffffff, mx, 1));
            mx = fmaxf(mx, __shfl_xor_sync(0xffffffff, mx, 2));
            const float mb = mx * sm_scale;
            uint32_t pb[5];
#pragma unroll
            for (int n = 0; n < 5; n++)
                pb[n] = pack_bf16(ex2_approx(fmaf(sc[n][0], sm_scale, -mb)), ex2_approx(fmaf(sc[n][1], sm_scale, -mb)));
            if (s < NSTEPS - 1) named_bar_arrive(10, 384);
            TSX(5);
            float oc[2][4];
#pragma unroll
            for (int i = 0; i < 4; i++) { oc[0][i] = oc[1][i] = 0.f; }
            mma_nv(oc[0], va[1][0], pb[2], pb[3]);
            mma_nv(oc[1], va[1][1], pb[2], pb[3]);
            mma_nv(oc[0], va[2][0], pb[4], 0u);
            mma_nv(oc[1], va[2][1], pb[4], 0u);
            float sm[4] = {0.f, 0.f, 0.f, 0.f};
            {
                const uint32_t ones[4] = {0x3F803F80u, 0x3F803F80u, 0x3F803F80u, 0x3F803F80u};
                mma_nv(sm, ones, pb[0], pb[1]);
                mma_nv(sm, ones, pb[2], pb[3]);
                mma_nv(sm, ones, pb[4], 0u);
            }
            const float i0 = __fdividef(1.0f, sm[0]), i1 = __fdividef(1.0f, sm[1]);
            TSX(6);
            mbar_wait(barV, par);
            TSX(7);
            ldmatrix_x4_t(va[0][0][0], va[0][0][1], va[0][0][2], va[0][0][3], sKV + vOff0);
            ldmatrix_x4_t(va[0][1][0], va[0][1][1], va[0][1][2], va[0][1][3], sKV + vOff1);
            if (leader) mbar_expect_tx(barV, 1024);
            if (sw == 1) asm volatile("ld.shared.v4.u32 {%0,%1,%2,%3}, [%4];" : "=r"(kvm.x), "=r"(kvm.y), "=r"(kvm.z), "=r"(kvm.w) : "r"(sKV + kvmOff) : "memory");
            mma_nv(oc[0], va[0][0], pb[0], pb[1]);
            mma_nv(oc[1], va[0][1], pb[0], pb[1]);
            stmatrix_x4_t(oDst, pack_bf16(oc[0][0] * i0, oc[0][1] * i1), pack_bf16(oc[0][2] * i0, oc[0][3] * i1),
                          pack_bf16(oc[1][0] * i0, oc[1][1] * i1), pack_bf16(oc[1][2] * i0, oc[1][3] * i1));
            if (s < NSTEPS - 1) named_bar_arrive(8, 384);
            TSX(8);
            *reinterpret_cast<uint4*>(kvmDst + (size_t)s * 65536) = kvm;
            if (p.seg_flags) { named_bar_sync(11, 128); if (leader) { __threadfence(); atomicAdd(p.seg_flags + s * 32, 1u); } }
            if (aw == 3 && lane == 0 && s + CH_NKV - 1 < NSTEPS) issue_kv(s + CH_NKV - 1);
        }
    }
    __syncthreads();
    TL_END(0);
    cluster_sync_all();
}

struct ChainFbParams {
    CUtensorMap tmW[3];
    CUtensorMap tmWo;
    CUtensorMap tmKV;
    const bf16* mem0;
    bf16* kvmem;
    float* part;
    uint4* membuf;
    const unsigned int* flags;
    unsigned int flag_target;
    unsigned int* seg_flags;
    long long* dbg;
};
constexpr int CF_MEM_STRIDE = 1040;
constexpr int CF_Q_STRIDE = 144;
constexpr int CF_O_STRIDE = 272;
constexpr int CF_NKV = 4;
constexpr int CF_KV_BYTES = 15360;
constexpr int CF_OFF_WO = 0;
constexpr int CF_OFF_WV = 65536;
constexpr int CF_OFF_KV = 131072;
constexpr int CF_OFF_MEM = CF_OFF_KV + CF_NKV * CF_KV_BYTES;
constexpr int CF_OFF_Q = CF_OFF_MEM + 8320;
constexpr int CF_OFF_O = CF_OFF_Q + 1152;
constexpr int CF_OFF_RED1 = CF_OFF_O + 2176;
constexpr int CF_OFF_SC = CF_OFF_RED1 + 6144;
constexpr int CF_OFF_RED2 = CF_OFF_SC + 1280;
constexpr int CF_OFF_ZERO = CF_OFF_RED2 + 2048;
constexpr int CF_OFF_BAR = CF_OFF_ZERO + 128;
constexpr int CF_SMEM = CF_OFF_BAR + 256;

__global__ void __launch_bounds__(384, 1) chain_fb_kernel(const __grid_constant__ ChainFbParams p) {
    extern __shared__ __align__(1024) unsigned char smem[];
    const uint32_t sb = smem_u32(smem);
    int tid; asm volatile("mov.u32 %0, %%tid.x;" : "=r"(tid));
    int bid; asm volatile("mov.u32 %0, %%ctaid.x;" : "=r"(bid));
    const int lane = tid & 31;
    const int warp = __shfl_sync(0xffffffff, tid >> 5, 0);
    const int wgi = __shfl_sync(0xffffffff, tid >> 7, 0);
    const int head = bid >> 1, half = bid & 1;
    const uint32_t barSc = sb + CF_OFF_BAR, barV = barSc + 8, barLd = barSc + 16, barKV = barSc + 24;

    if (tid == 0) {
        mbar_init(barSc, 1); mbar_init(barV, 1); mbar_init(barLd, 1);
        for (int i = 0; i < CF_NKV; i++) mbar_init(barKV + 8 * i, 1);
        fence_mbar_init();
        mbar_expect_tx(barSc, 1280);
        mbar_expect_tx(barV, 1024);
    }
    if (tid < 32) *reinterpret_cast<uint32_t*>(smem + CF_OFF_ZERO + tid * 4) = 0u;
    __syncthreads();
    cluster_sync_all();
    const uint32_t peer = half ^ 1;
    const int t4 = lane & 3, g8 = lane >> 2;
    const int lr = lane & 7, lm = lane >> 3;

    if (wgi < 2) {
        reg_alloc<208>();
        const int g = warp >> 1, kh = warp & 1;
        uint32_t wqk[2][16][4];
        {
            const int c64 = head * 2 + half;
            const int krow = lr + ((lane >> 4) & 1) * 8;
            const int chunk = g * 2 + (lm & 1);
            if (tid == 0) {
                mbar_expect_tx(barLd, 131072);
                tma_load_3d(sb + CF_OFF_WO, &p.tmW[0], 0, 0, c64, barLd);
                tma_load_3d(sb + CF_OFF_WO + 32768, &p.tmW[0], 0, 256, c64, barLd);
                tma_load_3d(sb + CF_OFF_WV, &p.tmW[1], 0, 0, c64, barLd);
                tma_load_3d(sb + CF_OFF_WV + 32768, &p.tmW[1], 0, 256, c64, barLd);
            }
            mbar_wait(barLd, 0);
#pragma unroll
            for (int m = 0; m < 2; m++)
#pragma unroll
                for (int ks = 0; ks < 16; ks++) {
                    int r = kh * 256 + ks * 16 + krow;
                    uint32_t addr = sb + (m == 0 ? CF_OFF_WO : CF_OFF_WV) + r * 128 + ((chunk ^ (r & 7)) << 4);
                    ldmatrix_x4_t(wqk[m][ks][0], wqk[m][ks][1], wqk[m][ks][2], wqk[m][ks][3], addr);
                }
            named_bar_sync(7, 256);
            if (tid == 0) {
                mbar_expect_tx(barLd, 131072);
                tma_load_3d(sb + CF_OFF_WV, &p.tmW[2], 0, 0, c64, barLd);
                tma_load_3d(sb + CF_OFF_WV + 32768, &p.tmW[2], 0, 256, c64, barLd);
                for (int i = 0; i < 4; i++) tma_load_3d(sb + CF_OFF_WO + i * 16384, &p.tmWo, 0, head * 128, half * 4 + i, barLd);
            }
            mbar_wait(barLd, 1);
            uint32_t f[16][4];
#pragma unroll
            for (int ks = 0; ks < 16; ks++) {
                int r = kh * 256 + ks * 16 + krow;
                ldmatrix_x4_t(f[ks][0], f[ks][1], f[ks][2], f[ks][3], sb + CF_OFF_WV + r * 128 + ((chunk ^ (r & 7)) << 4));
            }
            named_bar_sync(7, 256);
#pragma unroll
            for (int ks = 0; ks < 16; ks++)
                asm volatile("st.shared.v4.u32 [%0], {%1,%2,%3,%4};" :: "r"(sb + CF_OFF_WV + ((warp * 16 + ks) * 32 + lane) * 16), "r"(f[ks][0]), "r"(f[ks][1]), "r"(f[ks][2]), "r"(f[ks][3]) : "memory");
#pragma unroll
            for (int ks = 0; ks < 8; ks++)
#pragma unroll
                for (int mt = 0; mt < 2; mt++) {
                    int r = ks * 16 + krow;
                    int colchunk = warp * 4 + mt * 2 + (lm & 1);
                    ldmatrix_x4_t(f[ks * 2 + mt][0], f[ks * 2 + mt][1], f[ks * 2 + mt][2], f[ks * 2 + mt][3],
                                  sb + CF_OFF_WO + (colchunk >> 3) * 16384 + r * 128 + (((colchunk & 7) ^ (r & 7)) << 4));
                }
            named_bar_sync(7, 256);
#pragma unroll
            for (int i = 0; i < 16; i++)
                asm volatile("st.shared.v4.u32 [%0], {%1,%2,%3,%4};" :: "r"(sb + CF_OFF_WO + ((warp * 16 + i) * 32 + lane) * 16), "r"(f[i][0]), "r"(f[i][1]), "r"(f[i][2]), "r"(f[i][3]) : "memory");
            named_bar_sync(7, 256);
        }
        const uint32_t wvbase = sb + CF_OFF_WV + (warp * 16 * 32 + lane) * 16;
        const uint32_t wobase = sb + CF_OFF_WO + (warp * 16 * 32 + lane) * 16;
        const uint32_t bAddr = sb + CF_OFF_MEM + lr * CF_MEM_STRIDE + (kh * 256 + lm * 8) * 2;
        const uint32_t memDst = sb + CF_OFF_MEM + (tid & 7) * CF_MEM_STRIDE + (tid >> 3) * 16;
        const uint32_t redMine = sb + CF_OFF_RED1 + warp * 512 + lane * 16, redOther = sb + CF_OFF_RED1 + (warp ^ 1) * 512 + lane * 16;
        const uint32_t redV = sb + CF_OFF_RED1 + 4096 + g * 512 + lane * 16;
        const uint32_t qDst = sb + CF_OFF_Q + lr * CF_Q_STRIDE + (g * 16 + (lm & 1) * 8) * 2;
        const uint32_t kvOff = lr * 128 + (((g * 2 + (lm & 1)) ^ lr) << 4);
        const uint32_t peerBase = mapa_u32(sb, peer) - sb;
        const uint32_t oAddr = sb + CF_OFF_O + lr * CF_O_STRIDE + lm * 16;
        const uint4* memSrc = p.membuf + tid;
        float* partW = p.part + ((size_t)(half * 32 + warp * 4) * 32 + head) * 64 + lane * 2;
        const float* partR = p.part + (size_t)bid * (32 * 64) + tid * 4;
        uint4* memOut = p.membuf + bid * 8 + g8;

        for (int s = 0; s < NSTEPS; s++) {
            const uint32_t sKV = sb + CF_OFF_KV + (s & (CF_NKV - 1)) * CF_KV_BYTES;
            uint32_t wv[16][4];
#pragma unroll
            for (int i = 0; i < 12; i++) lds128(wv[i], wvbase + i * 512);
            {
                uint4 v0, v1;
                if (s == 0) {
                    v0 = *reinterpret_cast<const uint4*>(p.mem0 + (tid & 7) * 512 + (tid >> 3) * 8);
                    v1 = *reinterpret_cast<const uint4*>(p.mem0 + (tid & 7) * 512 + ((tid >> 3) + 32) * 8);
                } else {
                    const uint4* src = memSrc + (s - 1) * 512;
                    uint32_t n = 0;
                    do { v0 = ld_relaxed_v4(src); v1 = ld_relaxed_v4(src + 256); } while (POLL_B && (v0.x == 0u || v1.x == 0u) && ++n < (1u << 22));
                }
                asm volatile("st.shared.v4.u32 [%0], {%1,%2,%3,%4};" :: "r"(memDst), "r"(v0.x), "r"(v0.y), "r"(v0.z), "r"(v0.w) : "memory");
                asm volatile("st.shared.v4.u32 [%0], {%1,%2,%3,%4};" :: "r"(memDst + 512), "r"(v1.x), "r"(v1.y), "r"(v1.z), "r"(v1.w) : "memory");
            }
            named_bar_sync(7, 256);
            {
                float aq[2][4], ak[2][4];
#pragma unroll
                for (int i = 0; i < 4; i++) { aq[0][i] = aq[1][i] = ak[0][i] = ak[1][i] = 0.f; }
#pragma unroll
                for (int hb = 0; hb < 4; hb++) {
                    uint32_t b[2][4];
#pragma unroll
                    for (int kk = 0; kk < 2; kk++) ldmatrix_x4(b[kk][0], b[kk][1], b[kk][2], b[kk][3], bAddr + (hb * 2 + kk) * 64);
#pragma unroll
                    for (int kk = 0; kk < 2; kk++) {
                        const int k2 = (hb * 2 + kk) * 2;
                        mma_nv(aq[0], wqk[0][k2], b[kk][0], b[kk][1]);
                        mma_nv(ak[0], wqk[1][k2], b[kk][0], b[kk][1]);
                        mma_nv(aq[1], wqk[0][k2 + 1], b[kk][2], b[kk][3]);
                        mma_nv(ak[1], wqk[1][k2 + 1], b[kk][2], b[kk][3]);
                    }
                }
                float gv[4], kp[4];
#pragma unroll
                for (int i = 0; i < 4; i++) {
                    float q = aq[0][i] + aq[1][i], k = ak[0][i] + ak[1][i];
                    gv[i] = kh == 0 ? k : q;
                    kp[i] = kh == 0 ? q : k;
                }
                asm volatile("st.shared.v4.f32 [%0], {%1,%2,%3,%4};" :: "r"(redMine), "f"(gv[0]), "f"(gv[1]), "f"(gv[2]), "f"(gv[3]) : "memory");
                named_bar_sync(1 + g, 64);
                float o0, o1, o2, o3;
                asm volatile("ld.shared.v4.f32 {%0,%1,%2,%3}, [%4];" : "=f"(o0), "=f"(o1), "=f"(o2), "=f"(o3) : "r"(redOther) : "memory");
                uint32_t r0 = pack_bf16(kp[0] + o0, kp[1] + o1);
                uint32_t r1 = pack_bf16(kp[2] + o2, kp[3] + o3);
                asm volatile("stmatrix.sync.aligned.m8n8.x2.trans.shared.b16 [%0], {%1,%2};" :: "r"(kh == 0 ? qDst : sKV + kvOff), "r"(r0), "r"(r1) : "memory");
            }
            named_bar_arrive(5, 384);
            {
                float av[2][4];
#pragma unroll
                for (int i = 0; i < 4; i++) { av[0][i] = av[1][i] = 0.f; }
#pragma unroll
                for (int i = 12; i < 16; i++) lds128(wv[i], wvbase + i * 512);
#pragma unroll
                for (int hb = 0; hb < 2; hb++) {
                    uint32_t b[4][4];
#pragma unroll
                    for (int kk = 0; kk < 4; kk++) ldmatrix_x4(b[kk][0], b[kk][1], b[kk][2], b[kk][3], bAddr + (hb * 4 + kk) * 64);
#pragma unroll
                    for (int kk = 0; kk < 4; kk++) {
                        mma_nv(av[0], wv[(hb * 4 + kk) * 2], b[kk][0], b[kk][1]);
                        mma_nv(av[1], wv[(hb * 4 + kk) * 2 + 1], b[kk][2], b[kk][3]);
                    }
                }
#pragma unroll
                for (int i = 0; i < 4; i++) av[0][i] += av[1][i];
                if (kh == 1)
                    asm volatile("st.shared.v4.f32 [%0], {%1,%2,%3,%4};" :: "r"(redV), "f"(av[0][0]), "f"(av[0][1]), "f"(av[0][2]), "f"(av[0][3]) : "memory");
                named_bar_sync(1 + g, 64);
                if (kh == 0) {
                    float o0, o1, o2, o3;
                    asm volatile("ld.shared.v4.f32 {%0,%1,%2,%3}, [%4];" : "=f"(o0), "=f"(o1), "=f"(o2), "=f"(o3) : "r"(redV) : "memory");
                    uint32_t r0 = pack_bf16(av[0][0] + o0, av[0][1] + o1);
                    uint32_t r1 = pack_bf16(av[0][2] + o2, av[0][3] + o3);
                    const uint32_t vAddr = sKV + 5120 + half * 5120 + kvOff;
                    asm volatile("stmatrix.sync.aligned.m8n8.x2.trans.shared.b16 [%0], {%1,%2};" :: "r"(vAddr), "r"(r0), "r"(r1) : "memory");
                    __syncwarp();
                    if (lane < 16) {
                        uint32_t f[4];
                        lds128(f, vAddr);
                        st_async_v4(vAddr + peerBase, f[0], f[1], f[2], f[3], barV + peerBase);
                    }
                }
            }
            named_bar_arrive(6, 384);
            if (s == NSTEPS - 1) break;
            uint32_t wo[16][4];
#pragma unroll
            for (int i = 0; i < 16; i++) lds128(wo[i], wobase + i * 512);
            named_bar_sync(8, 384);
            const uint32_t tag = ((s >> 1) + 1) & 1;
            const uint32_t slotOff = (s & 1) * (64 * 32 * 64);
            {
                float a2[2][2][4];
#pragma unroll
                for (int i = 0; i < 4; i++) { a2[0][0][i] = a2[0][1][i] = a2[1][0][i] = a2[1][1][i] = 0.f; }
                uint32_t b[4][4];
#pragma unroll
                for (int kk = 0; kk < 4; kk++) ldmatrix_x4(b[kk][0], b[kk][1], b[kk][2], b[kk][3], oAddr + kk * 64);
#pragma unroll
                for (int kk = 0; kk < 4; kk++) {
                    mma_nv(a2[0][0], wo[kk * 4 + 0], b[kk][0], b[kk][1]);
                    mma_nv(a2[1][0], wo[kk * 4 + 1], b[kk][0], b[kk][1]);
                    mma_nv(a2[0][1], wo[kk * 4 + 2], b[kk][2], b[kk][3]);
                    mma_nv(a2[1][1], wo[kk * 4 + 3], b[kk][2], b[kk][3]);
                }
#pragma unroll
                for (int mt = 0; mt < 2; mt++) {
                    float c0 = a2[mt][0][0] + a2[mt][1][0], c1 = a2[mt][0][1] + a2[mt][1][1];
                    float c2 = a2[mt][0][2] + a2[mt][1][2], c3 = a2[mt][0][3] + a2[mt][1][3];
                    float* d = partW + slotOff + (mt * 2) * (32 * 64);
                    st_relaxed_v2(d, (__float_as_uint(c0) & ~1u) | tag, __float_as_uint(c1));
                    st_relaxed_v2(d + 32 * 64, (__float_as_uint(c2) & ~1u) | tag, __float_as_uint(c3));
                }
            }
            {
                const float* src = partR + slotOff;
                uint4 v0, v1;
                uint32_t n = 0;
                do { v0 = ld_relaxed_v4(src); v1 = ld_relaxed_v4(src + 1024); }
                while (POLL_R && ((((v0.x ^ tag) | (v1.x ^ tag)) | ((v0.z ^ tag) | (v1.z ^ tag))) & 1u) && ++n < (1u << 22));
                float f0 = __uint_as_float(v0.x) + __uint_as_float(v1.x), f1 = __uint_as_float(v0.y) + __uint_as_float(v1.y);
                float f2 = __uint_as_float(v0.z) + __uint_as_float(v1.z), f3 = __uint_as_float(v0.w) + __uint_as_float(v1.w);
                f0 += __shfl_xor_sync(0xffffffff, f0, 16); f1 += __shfl_xor_sync(0xffffffff, f1, 16);
                f2 += __shfl_xor_sync(0xffffffff, f2, 16); f3 += __shfl_xor_sync(0xffffffff, f3, 16);
                if (lane < 16) asm volatile("st.shared.v4.f32 [%0], {%1,%2,%3,%4};" :: "r"(sb + CF_OFF_RED2 + warp * 256 + lane * 16), "f"(f0), "f"(f1), "f"(f2), "f"(f3) : "memory");
                named_bar_sync(7, 256);
                if (warp == 0) {
                    float u[8][2];
                    const uint32_t ra = sb + CF_OFF_RED2 + ((2 * t4) * 8 + g8) * 4;
#pragma unroll
                    for (int w = 0; w < 8; w++) {
                        asm volatile("ld.shared.f32 %0, [%1];" : "=f"(u[w][0]) : "r"(ra + w * 256) : "memory");
                        asm volatile("ld.shared.f32 %0, [%1];" : "=f"(u[w][1]) : "r"(ra + w * 256 + 32) : "memory");
                    }
                    float a0 = ((u[0][0] + u[1][0]) + (u[2][0] + u[3][0])) + ((u[4][0] + u[5][0]) + (u[6][0] + u[7][0]));
                    float a1 = ((u[0][1] + u[1][1]) + (u[2][1] + u[3][1])) + ((u[4][1] + u[5][1]) + (u[6][1] + u[7][1]));
                    uint32_t m = pack_bf16(a0, a1);
                    uint32_t m1 = __shfl_down_sync(0xffffffff, m, 1), m2 = __shfl_down_sync(0xffffffff, m, 2), m3 = __shfl_down_sync(0xffffffff, m, 3);
                    if (t4 == 0) {
                        if (m == 0u) m = 0x8000u;
                        st_relaxed_v4(memOut + s * 512, m, m1, m2, m3);
                    }
                }
            }
        }
    } else {
        reg_dealloc<88>();
        const int aw = warp - 8;
        const uint32_t peerBase = mapa_u32(sb, peer) - sb;
        const float sm_scale = 0.08838834764831845f * 1.4426950408889634f;
        const int kc64 = 64 + head * 2 + half, vc64 = 128 + head * 2;
        auto issue_kv = [&](int s) {
            if ((s & 3) == 0) {
                uint32_t n = 0;
                while (ld_acquire_u32(p.flags + (s >> 2)) < p.flag_target) { if (++n > (1u << 22)) break; }
                fence_proxy_async_all();
            }
            int st = s & (CF_NKV - 1);
            uint32_t base = sb + CF_OFF_KV + st * CF_KV_BYTES;
            mbar_expect_tx(barKV + 8 * st, 12288);
            tma_load_3d(base + 1024, &p.tmKV, 0, s * 32, kc64, barKV + 8 * st);
            tma_load_3d(base + 5120 + 1024, &p.tmKV, 0, s * 32, vc64, barKV + 8 * st);
            tma_load_3d(base + 10240 + 1024, &p.tmKV, 0, s * 32, vc64 + 1, barKV + 8 * st);
        };
        if (aw == 3 && lane == 0) { for (int s = 0; s < CF_NKV - 1; s++) issue_kv(s); }
        const uint32_t kOff0 = lr * 128 + ((lm ^ lr) << 4), kOff1 = lr * 128 + (((4 + lm) ^ lr) << 4);
        const uint32_t qAddr = (lm & 1) ? (sb + CF_OFF_ZERO) : (sb + CF_OFF_Q + lr * CF_Q_STRIDE + (lm >> 1) * 16);
        const uint32_t qStep = (lm & 1) ? 0u : 32u;
        const uint32_t vRow = ((lm >> 1) * 8 + lr) * 128;
        const uint32_t vOff0 = 5120 + (aw >> 1) * 5120 + vRow + ((((aw & 1) * 4 + (lm & 1)) ^ lr) << 4);
        const uint32_t vOff1 = 5120 + (aw >> 1) * 5120 + vRow + ((((aw & 1) * 4 + 2 + (lm & 1)) ^ lr) << 4);
        const uint32_t padAdj = (lm >> 1) ? 2048u : 0u;
        const uint32_t scAddr = sb + CF_OFF_SC + lane * 8;
        const uint32_t oDst = sb + CF_OFF_O + lr * CF_O_STRIDE + (aw * 32 + lm * 8) * 2;
        const int si = tid - 256, sw = si >> 6, stok = (si >> 3) & 7, scn = si & 7;
        const uint32_t kvmOff = (sw == 0 ? 0u : 5120u + half * 5120u) + stok * 128 + ((scn ^ stok) << 4);
        bf16* kvmDst = p.kvmem + (size_t)stok * 8192 + sw * 4096 + head * 128 + half * 64 + scn * 8;
        const bool leader = (tid == 256);
        for (int s = 0; s < NSTEPS; s++) {
            const uint32_t par = s & 1;
            const int st = s & (CF_NKV - 1);
            const uint32_t sKV = sb + CF_OFF_KV + st * CF_KV_BYTES;
            mbar_wait(barKV + 8 * st, (s / CF_NKV) & 1);
            uint32_t kb[2][4][4], va[3][2][4];
#pragma unroll
            for (int n = 0; n < 4; n++) {
                ldmatrix_x4(kb[0][n][0], kb[0][n][1], kb[0][n][2], kb[0][n][3], sKV + (n + 1) * 1024 + kOff0);
                ldmatrix_x4(kb[1][n][0], kb[1][n][1], kb[1][n][2], kb[1][n][3], sKV + (n + 1) * 1024 + kOff1);
            }
            named_bar_sync(5, 384);
            float sc[5][4];
#pragma unroll
            for (int n = 0; n < 5; n++) { sc[n][0] = sc[n][1] = sc[n][2] = sc[n][3] = 0.f; }
            {
                uint32_t a[4][4], km[2][4];
#pragma unroll
                for (int k = 0; k < 4; k++) ldmatrix_x4(a[k][0], a[k][1], a[k][2], a[k][3], qAddr + k * qStep);
                ldmatrix_x4(km[0][0], km[0][1], km[0][2], km[0][3], sKV + kOff0);
                ldmatrix_x4(km[1][0], km[1][1], km[1][2], km[1][3], sKV + kOff1);
#pragma unroll
                for (int kp = 0; kp < 2; kp++) {
#pragma unroll
                    for (int n = 0; n < 4; n++) mma_nv(sc[n + 1], a[kp * 2], kb[kp][n][0], kb[kp][n][1]);
#pragma unroll
                    for (int n = 0; n < 4; n++) mma_nv(sc[n + 1], a[kp * 2 + 1], kb[kp][n][2], kb[kp][n][3]);
                }
                mma_nv(sc[0], a[0], km[0][0], km[0][1]);
                mma_nv(sc[0], a[1], km[0][2], km[0][3]);
                mma_nv(sc[0], a[2], km[1][0], km[1][1]);
                mma_nv(sc[0], a[3], km[1][2], km[1][3]);
            }
            if (aw == 0) {
#pragma unroll
                for (int n = 0; n < 5; n++) st_async_v2(scAddr + peerBase + n * 256, __float_as_uint(sc[n][0]), __float_as_uint(sc[n][1]), barSc + peerBase);
            }
#pragma unroll
            for (int ks = 1; ks < 3; ks++) {
                const uint32_t adj = ks == 2 ? padAdj : 0u;
                ldmatrix_x4_t(va[ks][0][0], va[ks][0][1], va[ks][0][2], va[ks][0][3], sKV + ks * 2048 + vOff0 - adj);
                ldmatrix_x4_t(va[ks][1][0], va[ks][1][1], va[ks][1][2], va[ks][1][3], sKV + ks * 2048 + vOff1 - adj);
            }
            uint4 kvm;
            if (sw == 0) asm volatile("ld.shared.v4.u32 {%0,%1,%2,%3}, [%4];" : "=r"(kvm.x), "=r"(kvm.y), "=r"(kvm.z), "=r"(kvm.w) : "r"(sKV + kvmOff) : "memory");
            mbar_wait(barSc, par);
            float pp[5][2];
#pragma unroll
            for (int n = 0; n < 5; n++)
                asm volatile("ld.shared.v2.f32 {%0,%1}, [%2];" : "=f"(pp[n][0]), "=f"(pp[n][1]) : "r"(scAddr + n * 256) : "memory");
            if (leader) mbar_expect_tx(barSc, 1280);
#pragma unroll
            for (int n = 0; n < 5; n++) { sc[n][0] += pp[n][0]; sc[n][1] += pp[n][1]; }
            float mx = fmaxf(fmaxf(fmaxf(sc[0][0], sc[0][1]), fmaxf(sc[1][0], sc[1][1])), fmaxf(fmaxf(sc[2][0], sc[2][1]), fmaxf(sc[3][0], sc[3][1])));
            mx = fmaxf(mx, fmaxf(sc[4][0], sc[4][1]));
            mx = fmaxf(mx, __shfl_xor_sync(0xffffffff, mx, 1));
            mx = fmaxf(mx, __shfl_xor_sync(0xffffffff, mx, 2));
            const float mb = mx * sm_scale;
            uint32_t pb[5];
            float e[5][2];
#pragma unroll
            for (int n = 0; n < 5; n++) {
                e[n][0] = ex2_approx(fmaf(sc[n][0], sm_scale, -mb));
                e[n][1] = ex2_approx(fmaf(sc[n][1], sm_scale, -mb));
                pb[n] = pack_bf16(e[n][0], e[n][1]);
            }
            float oc[2][4];
#pragma unroll
            for (int i = 0; i < 4; i++) { oc[0][i] = oc[1][i] = 0.f; }
            mma_nv(oc[0], va[1][0], pb[2], pb[3]);
            mma_nv(oc[1], va[1][1], pb[2], pb[3]);
            mma_nv(oc[0], va[2][0], pb[4], 0u);
            mma_nv(oc[1], va[2][1], pb[4], 0u);
            float sum = ((e[0][0] + e[0][1]) + (e[1][0] + e[1][1])) + ((e[2][0] + e[2][1]) + (e[3][0] + e[3][1])) + (e[4][0] + e[4][1]);
            sum += __shfl_xor_sync(0xffffffff, sum, 1);
            sum += __shfl_xor_sync(0xffffffff, sum, 2);
            const float inv = __fdividef(1.0f, sum);
            const float i0 = __shfl_sync(0xffffffff, inv, t4 * 8), i1 = __shfl_sync(0xffffffff, inv, t4 * 8 + 4);
            named_bar_sync(6, 384);
            mbar_wait(barV, par);
            ldmatrix_x4_t(va[0][0][0], va[0][0][1], va[0][0][2], va[0][0][3], sKV + vOff0);
            ldmatrix_x4_t(va[0][1][0], va[0][1][1], va[0][1][2], va[0][1][3], sKV + vOff1);
            if (leader) mbar_expect_tx(barV, 1024);
            if (sw == 1) asm volatile("ld.shared.v4.u32 {%0,%1,%2,%3}, [%4];" : "=r"(kvm.x), "=r"(kvm.y), "=r"(kvm.z), "=r"(kvm.w) : "r"(sKV + kvmOff) : "memory");
            mma_nv(oc[0], va[0][0], pb[0], pb[1]);
            mma_nv(oc[1], va[0][1], pb[0], pb[1]);
            stmatrix_x4_t(oDst, pack_bf16(oc[0][0] * i0, oc[0][1] * i1), pack_bf16(oc[0][2] * i0, oc[0][3] * i1),
                          pack_bf16(oc[1][0] * i0, oc[1][1] * i1), pack_bf16(oc[1][2] * i0, oc[1][3] * i1));
            if (s < NSTEPS - 1) named_bar_arrive(8, 384);
            *reinterpret_cast<uint4*>(kvmDst + (size_t)s * 65536) = kvm;
            if (p.seg_flags) { named_bar_sync(11, 128); if (leader) { __threadfence(); atomicAdd(p.seg_flags + s * 32, 1u); } }
            if (aw == 3 && lane == 0 && s + CF_NKV - 1 < NSTEPS) issue_kv(s + CF_NKV - 1);
        }
    }
    __syncthreads();
    cluster_sync_all();
}

struct AttnAParams {
    CUtensorMap tmKV;
    const bf16* qkv;
    bf16* o;
};
constexpr int AA_KT = 256;
constexpr int AA_NST = 3;
constexpr int AA_SMEM = AA_NST * 2 * AA_KT * 32 + 64;

__device__ __forceinline__ float ex2a(float x) { float y; asm("ex2.approx.ftz.f32 %0, %1;" : "=f"(y) : "f"(x)); return y; }
__device__ __forceinline__ void mma_f(float* c, const uint32_t* a, uint32_t b0, uint32_t b1) {
    asm("mma.sync.aligned.m16n8k16.row.col.f32.bf16.bf16.f32 {%0,%1,%2,%3}, {%4,%5,%6,%7}, {%8,%9}, {%0,%1,%2,%3};"
        : "+f"(c[0]), "+f"(c[1]), "+f"(c[2]), "+f"(c[3]) : "r"(a[0]), "r"(a[1]), "r"(a[2]), "r"(a[3]), "r"(b0), "r"(b1));
}

__global__ void __launch_bounds__(256, 2) attn_a_kernel(const __grid_constant__ AttnAParams p) {
    extern __shared__ __align__(1024) unsigned char smem[];
    const uint32_t sb = smem_u32(smem);
    const uint32_t bars = sb + AA_NST * 2 * AA_KT * 32;
    const int tid = threadIdx.x, lane = tid & 31, warp = tid >> 5;
    const int head = blockIdx.x >> 3, qt = blockIdx.x & 7;
    const int t4 = lane & 3, g8 = lane >> 2;
    constexpr int NT = 2048 / AA_KT;
    TL_START(4);

    if (tid == 0) {
        for (int i = 0; i < AA_NST; i++) { mbar_init(bars + 8 * i, 1); mbar_init(bars + 8 * (AA_NST + i), 8); }
        fence_mbar_init();
    }
    __syncthreads();
    auto issue = [&](int t) {
        int st = t % AA_NST;
        uint32_t dst = sb + st * (2 * AA_KT * 32);
        mbar_expect_tx(bars + 8 * st, 2 * AA_KT * 32);
        tma_load_2d(dst, &p.tmKV, 512 + head * 16, t * AA_KT, bars + 8 * st);
        tma_load_2d(dst + AA_KT * 32, &p.tmKV, 1024 + head * 16, t * AA_KT, bars + 8 * st);
    };
    if (tid == 0) { for (int t = 0; t < AA_NST; t++) issue(t); }

    uint32_t qa[2][4];
    const int row0 = qt * 256 + warp * 32;
#pragma unroll
    for (int m = 0; m < 2; m++) {
        const bf16* q = p.qkv + (size_t)(row0 + m * 16 + g8) * 1536 + head * 16 + t4 * 2;
        qa[m][0] = *reinterpret_cast<const uint32_t*>(q);
        qa[m][1] = *reinterpret_cast<const uint32_t*>(q + 8 * 1536);
        qa[m][2] = *reinterpret_cast<const uint32_t*>(q + 8);
        qa[m][3] = *reinterpret_cast<const uint32_t*>(q + 8 * 1536 + 8);
    }
    const float sc = 0.25f * 1.4426950408889634f;
    float mrow[2][2], oacc[2][2][4], lacc[2][4];
#pragma unroll
    for (int m = 0; m < 2; m++) {
        mrow[m][0] = mrow[m][1] = -3.0e38f;
#pragma unroll
        for (int i = 0; i < 4; i++) { oacc[m][0][i] = oacc[m][1][i] = 0.f; lacc[m][i] = 0.f; }
    }
    const uint32_t ones = 0x3F803F80u;
    const int lr = lane & 7, lm = lane >> 3;
    const int krow = (lm >> 1) * 8 + lr, kch = lm & 1;
    const uint32_t koff = krow * 32 + ((kch ^ ((krow >> 2) & 1)) << 4);
    const int vrow = (lm & 1) * 8 + lr, vch = lm >> 1;
    const uint32_t voff = vrow * 32 + ((vch ^ ((vrow >> 2) & 1)) << 4);

    for (int t = 0; t < NT; t++) {
        const int st = t % AA_NST;
        mbar_wait(bars + 8 * st, (t / AA_NST) & 1);
        const uint32_t sK = sb + st * (2 * AA_KT * 32), sV = sK + AA_KT * 32;
#pragma unroll 1
        for (int kb = 0; kb < AA_KT / 64; kb++) {
            float s[2][8][4];
#pragma unroll
            for (int np = 0; np < 4; np++) {
                uint32_t b0, b1, b2, b3;
                ldmatrix_x4(b0, b1, b2, b3, sK + (kb * 64 + np * 16) * 32 + koff);
#pragma unroll
                for (int m = 0; m < 2; m++) {
#pragma unroll
                    for (int i = 0; i < 4; i++) { s[m][np * 2][i] = 0.f; s[m][np * 2 + 1][i] = 0.f; }
                    mma_f(s[m][np * 2], qa[m], b0, b1);
                    mma_f(s[m][np * 2 + 1], qa[m], b2, b3);
                }
            }
            uint32_t pa[2][4][4];
#pragma unroll
            for (int m = 0; m < 2; m++) {
                float mx0 = s[m][0][0], mx1 = s[m][0][2];
#pragma unroll
                for (int n = 0; n < 8; n++) {
                    mx0 = fmaxf(mx0, fmaxf(s[m][n][0], s[m][n][1]));
                    mx1 = fmaxf(mx1, fmaxf(s[m][n][2], s[m][n][3]));
                }
                mx0 = fmaxf(mx0, __shfl_xor_sync(0xffffffff, mx0, 1)); mx0 = fmaxf(mx0, __shfl_xor_sync(0xffffffff, mx0, 2));
                mx1 = fmaxf(mx1, __shfl_xor_sync(0xffffffff, mx1, 1)); mx1 = fmaxf(mx1, __shfl_xor_sync(0xffffffff, mx1, 2));
                const float mn0 = fmaxf(mrow[m][0], mx0), mn1 = fmaxf(mrow[m][1], mx1);
                const float a0 = ex2a((mrow[m][0] - mn0) * sc), a1 = ex2a((mrow[m][1] - mn1) * sc);
                mrow[m][0] = mn0; mrow[m][1] = mn1;
                const float mb0 = mn0 * sc, mb1 = mn1 * sc;
#pragma unroll
                for (int d = 0; d < 2; d++) { oacc[m][d][0] *= a0; oacc[m][d][1] *= a0; oacc[m][d][2] *= a1; oacc[m][d][3] *= a1; }
                lacc[m][0] *= a0; lacc[m][2] *= a1;
#pragma unroll
                for (int n = 0; n < 8; n++) {
                    float p0 = ex2a(fmaf(s[m][n][0], sc, -mb0)), p1 = ex2a(fmaf(s[m][n][1], sc, -mb0));
                    float p2 = ex2a(fmaf(s[m][n][2], sc, -mb1)), p3 = ex2a(fmaf(s[m][n][3], sc, -mb1));
                    pa[m][n >> 1][(n & 1) * 2 + 0] = pack_bf16(p0, p1);
                    pa[m][n >> 1][(n & 1) * 2 + 1] = pack_bf16(p2, p3);
                }
            }
#pragma unroll
            for (int ks = 0; ks < 4; ks++) {
                uint32_t b0, b1, b2, b3;
                ldmatrix_x4_t(b0, b1, b2, b3, sV + (kb * 64 + ks * 16) * 32 + voff);
#pragma unroll
                for (int m = 0; m < 2; m++) {
                    mma_f(oacc[m][0], pa[m][ks], b0, b1);
                    mma_f(oacc[m][1], pa[m][ks], b2, b3);
                    mma_f(lacc[m], pa[m][ks], ones, ones);
                }
            }
        }
        __syncwarp();
        if (lane == 0) mbar_arrive(bars + 8 * (AA_NST + st));
        if (tid == 0 && t + AA_NST < NT) {
            mbar_wait(bars + 8 * (AA_NST + st), (t / AA_NST) & 1);
            issue(t + AA_NST);
        }
    }
#pragma unroll
    for (int m = 0; m < 2; m++) {
        const float i0 = 1.0f / lacc[m][0], i1 = 1.0f / lacc[m][2];
        bf16* o = p.o + (size_t)(row0 + m * 16 + g8) * 512 + head * 16 + t4 * 2;
#pragma unroll
        for (int d = 0; d < 2; d++) {
            *reinterpret_cast<uint32_t*>(o + d * 8) = pack_bf16(oacc[m][d][0] * i0, oacc[m][d][1] * i0);
            *reinterpret_cast<uint32_t*>(o + 8 * 512 + d * 8) = pack_bf16(oacc[m][d][2] * i1, oacc[m][d][3] * i1);
        }
    }
    TL_END(4);
}

struct AttnBParams {
    CUtensorMap tmQKV;
    CUtensorMap tmKVM;
    CUtensorMap tmO;
    const unsigned int* seg_flags;
    unsigned int seg_target;
    unsigned int* tile_flags;
};
constexpr int AB_WARP_BYTES = 28672;
constexpr int AB_SMEM = 4 * AB_WARP_BYTES + 64;

__global__ void __launch_bounds__(128, 2) attn_b_kernel(const __grid_constant__ AttnBParams p) {
    extern __shared__ __align__(1024) unsigned char smem[];
    const int tid = threadIdx.x, lane = tid & 31, warp = tid >> 5;
    const uint32_t sb = smem_u32(smem) + warp * AB_WARP_BYTES;
    const uint32_t bar = smem_u32(smem) + 4 * AB_WARP_BYTES + warp * 8;
    const int t4 = lane & 3, g8 = lane >> 2;
    TL_START(6);
    if (lane == 0) { mbar_init(bar, 1); fence_mbar_init(); }
    __syncwarp();
    uint32_t phase = 0;
    for (int task = blockIdx.x; task < 512; task += gridDim.x, phase ^= 1) {
    const int seg = task >> 3, head = (task & 7) * 4 + warp;
    const uint32_t sQ = sb, sK = sb + 8192, sV = sb + 16384, sKm = sb + 24576, sVm = sb + 26624;
    if (lane == 0) {
        fence_proxy_async_all();
        mbar_expect_tx(bar, AB_WARP_BYTES);
#pragma unroll
        for (int h = 0; h < 2; h++) {
            tma_load_3d(sQ + h * 4096, &p.tmQKV, 0, seg * 32, head * 2 + h, bar);
            tma_load_3d(sK + h * 4096, &p.tmQKV, 0, seg * 32, 64 + head * 2 + h, bar);
            tma_load_3d(sV + h * 4096, &p.tmQKV, 0, seg * 32, 128 + head * 2 + h, bar);
        }
    }
    if (tid == 0 && p.seg_flags) {
        uint32_t n = 0;
        while (ld_acquire_u32(p.seg_flags + seg * 32) < p.seg_target) { if (++n > (1u << 22)) break; __nanosleep(400); }
    }
    __syncthreads();
    if (lane == 0) {
        fence_proxy_async_all();
#pragma unroll
        for (int h = 0; h < 2; h++) {
            tma_load_3d(sKm + h * 1024, &p.tmKVM, 0, seg * 8, head * 2 + h, bar);
            tma_load_3d(sVm + h * 1024, &p.tmKVM, 0, seg * 8, 64 + head * 2 + h, bar);
        }
    }
    __syncwarp();
    mbar_wait(bar, phase);
    const int lr = lane & 7, lm = lane >> 3;
    float s[2][5][4];
#pragma unroll
    for (int m = 0; m < 2; m++)
#pragma unroll
        for (int n = 0; n < 5; n++)
#pragma unroll
            for (int i = 0; i < 4; i++) s[m][n][i] = 0.f;
#pragma unroll
    for (int kp = 0; kp < 4; kp++) {
        const int hb = kp >> 1, c0 = (kp & 1) * 4;
        uint32_t a[2][2][4];
#pragma unroll
        for (int m = 0; m < 2; m++)
#pragma unroll
            for (int ks = 0; ks < 2; ks++) {
                int row = m * 16 + (lm & 1) * 8 + lr, ch = c0 + ks * 2 + (lm >> 1);
                ldmatrix_x4(a[m][ks][0], a[m][ks][1], a[m][ks][2], a[m][ks][3], sQ + hb * 4096 + row * 128 + ((ch ^ (row & 7)) << 4));
            }
#pragma unroll
        for (int n = 0; n < 5; n++) {
            uint32_t b0, b1, b2, b3;
            int ch = c0 + lm;
            if (n == 0) ldmatrix_x4(b0, b1, b2, b3, sKm + hb * 1024 + lr * 128 + ((ch ^ lr) << 4));
            else { int row = (n - 1) * 8 + lr; ldmatrix_x4(b0, b1, b2, b3, sK + hb * 4096 + row * 128 + ((ch ^ (row & 7)) << 4)); }
#pragma unroll
            for (int m = 0; m < 2; m++) { mma_f(s[m][n], a[m][0], b0, b1); mma_f(s[m][n], a[m][1], b2, b3); }
        }
    }
    const float sc = 0.08838834764831845f * 1.4426950408889634f;
    uint32_t pa[2][3][4];
    float inv[2][2];
#pragma unroll
    for (int m = 0; m < 2; m++) {
        const int r0 = m * 16 + g8, r1 = r0 + 8;
        float mx0 = -3.0e38f, mx1 = -3.0e38f;
#pragma unroll
        for (int n = 0; n < 5; n++) {
            if (n > 0) {
                int j = (n - 1) * 8 + t4 * 2;
                if (j > r0) s[m][n][0] = -3.0e38f;
                if (j + 1 > r0) s[m][n][1] = -3.0e38f;
                if (j > r1) s[m][n][2] = -3.0e38f;
                if (j + 1 > r1) s[m][n][3] = -3.0e38f;
            }
            mx0 = fmaxf(mx0, fmaxf(s[m][n][0], s[m][n][1]));
            mx1 = fmaxf(mx1, fmaxf(s[m][n][2], s[m][n][3]));
        }
        mx0 = fmaxf(mx0, __shfl_xor_sync(0xffffffff, mx0, 1)); mx0 = fmaxf(mx0, __shfl_xor_sync(0xffffffff, mx0, 2));
        mx1 = fmaxf(mx1, __shfl_xor_sync(0xffffffff, mx1, 1)); mx1 = fmaxf(mx1, __shfl_xor_sync(0xffffffff, mx1, 2));
        const float mb0 = mx0 * sc, mb1 = mx1 * sc;
        float l0 = 0.f, l1 = 0.f;
#pragma unroll
        for (int n = 0; n < 5; n++) {
            s[m][n][0] = ex2a(fmaf(s[m][n][0], sc, -mb0)); s[m][n][1] = ex2a(fmaf(s[m][n][1], sc, -mb0));
            s[m][n][2] = ex2a(fmaf(s[m][n][2], sc, -mb1)); s[m][n][3] = ex2a(fmaf(s[m][n][3], sc, -mb1));
            l0 += s[m][n][0] + s[m][n][1]; l1 += s[m][n][2] + s[m][n][3];
        }
        l0 += __shfl_xor_sync(0xffffffff, l0, 1); l0 += __shfl_xor_sync(0xffffffff, l0, 2);
        l1 += __shfl_xor_sync(0xffffffff, l1, 1); l1 += __shfl_xor_sync(0xffffffff, l1, 2);
        inv[m][0] = 1.0f / l0; inv[m][1] = 1.0f / l1;
#pragma unroll
        for (int n = 0; n < 5; n++) {
            pa[m][n >> 1][(n & 1) * 2 + 0] = pack_bf16(s[m][n][0] * inv[m][0], s[m][n][1] * inv[m][0]);
            pa[m][n >> 1][(n & 1) * 2 + 1] = pack_bf16(s[m][n][2] * inv[m][1], s[m][n][3] * inv[m][1]);
        }
        pa[m][2][2] = 0u; pa[m][2][3] = 0u;
    }
    __syncwarp();
#pragma unroll
    for (int dq = 0; dq < 4; dq++) {
        float oc[2][4][4];
#pragma unroll
        for (int m = 0; m < 2; m++)
#pragma unroll
            for (int n = 0; n < 4; n++)
#pragma unroll
                for (int i = 0; i < 4; i++) oc[m][n][i] = 0.f;
        const int hb = dq >> 1, c0 = (dq & 1) * 4;
#pragma unroll
        for (int ks = 0; ks < 3; ks++) {
#pragma unroll
            for (int dp = 0; dp < 2; dp++) {
                int key = ks * 16 + (lm & 1) * 8 + lr, ch = c0 + dp * 2 + (lm >> 1);
                uint32_t addr;
                if (key < 8 || key >= 40) addr = sVm + hb * 1024 + lr * 128 + ((ch ^ lr) << 4);
                else { int row = key - 8; addr = sV + hb * 4096 + row * 128 + ((ch ^ (row & 7)) << 4); }
                uint32_t b0, b1, b2, b3;
                ldmatrix_x4_t(b0, b1, b2, b3, addr);
#pragma unroll
                for (int m = 0; m < 2; m++) { mma_f(oc[m][dp * 2], pa[m][ks], b0, b1); mma_f(oc[m][dp * 2 + 1], pa[m][ks], b2, b3); }
            }
        }
#pragma unroll
        for (int m = 0; m < 2; m++)
#pragma unroll
            for (int dp = 0; dp < 2; dp++) {
                int row = m * 16 + (lm & 1) * 8 + lr, ch = c0 + dp * 2 + (lm >> 1);
                stmatrix_x4(sQ + hb * 4096 + row * 128 + ((ch ^ (row & 7)) << 4),
                            pack_bf16(oc[m][dp * 2][0], oc[m][dp * 2][1]), pack_bf16(oc[m][dp * 2][2], oc[m][dp * 2][3]),
                            pack_bf16(oc[m][dp * 2 + 1][0], oc[m][dp * 2 + 1][1]), pack_bf16(oc[m][dp * 2 + 1][2], oc[m][dp * 2 + 1][3]));
            }
    }
    fence_proxy_async_smem();
    __syncwarp();
    if (lane == 0) {
        tma_store_3d(&p.tmO, sQ, 0, seg * 32, head * 2);
        tma_store_3d(&p.tmO, sQ + 4096, 0, seg * 32, head * 2 + 1);
        bulk_commit();
        bulk_wait_all0();
        fence_proxy_async_all();
        __threadfence();
        atomicAdd(p.tile_flags + (seg >> 2), 1u);
    }
    __syncwarp();
    }
    TL_END(6);
}

struct GemmSParams {
    CUtensorMap tmA;
    CUtensorMap tmB;
    CUtensorMap tmC;
    int n_tiles;
    int m_tiles;
    bf16* c; int ldc;
    int kblocks_half;
    int c_col64;
    const unsigned int* tile_flags;
    unsigned int tile_target;
};
constexpr int GS_NST = 5;
constexpr int GS_SMEM = GS_NST * 32768 + 32768 + 256;

__global__ void __launch_bounds__(288, 1) gemm_s_kernel(const __grid_constant__ GemmSParams p) {
    extern __shared__ __align__(1024) unsigned char smem[];
    const uint32_t sS = smem_u32(smem);
    const uint32_t sR = sS + GS_NST * 32768;
    const uint32_t bars = sR + 32768;
    const uint32_t barFull = bars, barEmpty = bars + 8 * GS_NST, barRed = bars + 16 * GS_NST, barFree = barRed + 8;
    const int warp = __shfl_sync(0xffffffff, threadIdx.x >> 5, 0), lane = threadIdx.x & 31;
    const int kh = blockIdx.x & 1;
    const int ntiles = p.m_tiles * p.n_tiles, ncl = gridDim.x >> 1;
    TL_START(7);
    if (threadIdx.x == 0) {
        for (int i = 0; i < GS_NST; i++) { mbar_init(barFull + 8 * i, 1); mbar_init(barEmpty + 8 * i, 8); }
        mbar_init(barRed, 1);
        mbar_init(barFree, 1);
        fence_mbar_init();
        mbar_expect_tx(barRed, 32768);
    }
    __syncthreads();
    cluster_sync_all();
    if (warp == 8) {
        if (lane == 0) {
            int it = 0;
            for (int tile = blockIdx.x >> 1; tile < ntiles; tile += ncl) {
                const int mt = tile / p.n_tiles, nt = tile % p.n_tiles;
                {
                    uint32_t n = 0;
                    while (ld_acquire_u32(p.tile_flags + mt) < p.tile_target) { if (++n > (1u << 22)) break; __nanosleep(500); }
                    fence_proxy_async_all();
                }
                for (int i = 0; i < p.kblocks_half; i++, it++) {
                    int slot = it % GS_NST;
                    if (it >= GS_NST) mbar_wait(barEmpty + 8 * slot, ((it / GS_NST) - 1) & 1);
                    mbar_expect_tx(barFull + 8 * slot, 32768);
                    int kb = kh * p.kblocks_half + i;
                    tma_load_3d(sS + slot * 32768, &p.tmA, 0, mt * 128, kb, barFull + 8 * slot);
                    tma_load_3d(sS + slot * 32768 + 16384, &p.tmB, 0, kb * 64, nt * 2, barFull + 8 * slot);
                }
            }
        }
    } else {
        const int wg = warp >> 2, wq = warp & 3;
        const uint32_t peer = kh ^ 1;
        const uint32_t rbuf = mapa_u32(sR, peer), rbar = mapa_u32(barRed, peer), rfree = mapa_u32(barFree, peer);
        const int tw = threadIdx.x;
        int it = 0, nt_done = 0;
        for (int tile = blockIdx.x >> 1; tile < ntiles; tile += ncl, nt_done++) {
            const int mt = tile / p.n_tiles, nt = tile % p.n_tiles;
            float acc[64];
            int prev = 0;
            for (int i = 0; i < p.kblocks_half; i++, it++) {
                int slot = it % GS_NST;
                mbar_wait(barFull + 8 * slot, (it / GS_NST) & 1);
                wg_fence();
                uint64_t da = make_desc(sS + slot * 32768 + wg * 8192, 16, 1024);
                uint64_t db = make_desc(sS + slot * 32768 + 16384, 8192, 1024);
#pragma unroll
                for (int kk = 0; kk < 4; kk++)
                    wgmma_m64n128k16_ss_tb(acc, da + (uint64_t)(kk * 2), db + (uint64_t)(kk * 128), (i | kk) != 0);
                wg_commit();
                if (i > 0) { wg_wait<1>(); if (lane == 0) mbar_arrive(barEmpty + 8 * prev); }
                prev = slot;
            }
            wg_wait<0>();
            if (lane == 0) mbar_arrive(barEmpty + 8 * prev);
            if (nt_done > 0) mbar_wait(barFree, (nt_done - 1) & 1);
#pragma unroll
            for (int j = 0; j < 8; j++) {
                float a[4];
#pragma unroll
                for (int i = 0; i < 4; i++) a[i] = kh == 0 ? acc[(8 + j) * 4 + i] : acc[j * 4 + i];
                st_async_v4(rbuf + (j * 256 + tw) * 16, __float_as_uint(a[0]), __float_as_uint(a[1]), __float_as_uint(a[2]), __float_as_uint(a[3]), rbar);
            }
            mbar_wait(barRed, nt_done & 1);
            uint32_t r[4][4];
#pragma unroll
            for (int c = 0; c < 4; c++)
#pragma unroll
                for (int e = 0; e < 2; e++) {
                    int j = c * 2 + e;
                    float4 v;
                    asm volatile("ld.shared.v4.f32 {%0,%1,%2,%3}, [%4];" : "=f"(v.x), "=f"(v.y), "=f"(v.z), "=f"(v.w) : "r"(sR + (j * 256 + tw) * 16) : "memory");
                    float a[4];
#pragma unroll
                    for (int i = 0; i < 4; i++) a[i] = kh == 0 ? acc[j * 4 + i] : acc[(8 + j) * 4 + i];
                    r[c][e * 2 + 0] = pack_bf16(a[0] + v.x, a[1] + v.y);
                    r[c][e * 2 + 1] = pack_bf16(a[2] + v.z, a[3] + v.w);
                }
            named_bar_sync(1, 256);
            if (tw == 0) {
                mbar_expect_tx(barRed, 32768);
                asm volatile("mbarrier.arrive.release.cluster.shared::cluster.b64 _, [%0];" :: "r"(rfree) : "memory");
            }
            bf16* cbase = p.c + (size_t)(mt * 128 + wg * 64 + wq * 16 + (lane >> 2)) * p.ldc + p.c_col64 * 64 + nt * 128 + kh * 64 + (lane & 3) * 2;
#pragma unroll
            for (int c = 0; c < 4; c++)
#pragma unroll
                for (int e = 0; e < 2; e++) {
                    *reinterpret_cast<uint32_t*>(cbase + (c * 2 + e) * 8) = r[c][e * 2 + 0];
                    *reinterpret_cast<uint32_t*>(cbase + 8 * p.ldc + (c * 2 + e) * 8) = r[c][e * 2 + 1];
                }
        }
    }
    TL_END(7);
    __syncthreads();
    cluster_sync_all();
}

typedef CUresult (*PFN_encodeTiled)(CUtensorMap*, CUtensorMapDataType, cuuint32_t, void*, const cuuint64_t*, const cuuint64_t*,
                                    const cuuint32_t*, const cuuint32_t*, CUtensorMapInterleave, CUtensorMapSwizzle,
                                    CUtensorMapL2promotion, CUtensorMapFloatOOBfill);
static PFN_encodeTiled g_encode = nullptr;
static void init_encode() {
    if (g_encode) return;
    void* fn = nullptr;
    cudaDriverEntryPointQueryResult st;
    cudaGetDriverEntryPoint("cuTensorMapEncodeTiled", &fn, cudaEnableDefault, &st);
    g_encode = (PFN_encodeTiled)fn;
}
static CUtensorMap make_tmap_3d64(const void* ptr, uint64_t rows, uint64_t cols, uint64_t ld, uint32_t box_rows, uint32_t box_c64) {
    CUtensorMap tm;
    cuuint64_t dims[3] = {64, rows, cols / 64};
    cuuint64_t strides[2] = {ld * 2, 128};
    cuuint32_t box[3] = {64, box_rows, box_c64};
    cuuint32_t es[3] = {1, 1, 1};
    g_encode(&tm, CU_TENSOR_MAP_DATA_TYPE_BFLOAT16, 3, (void*)ptr, dims, strides, box, es, CU_TENSOR_MAP_INTERLEAVE_NONE,
             CU_TENSOR_MAP_SWIZZLE_128B, CU_TENSOR_MAP_L2_PROMOTION_L2_128B, CU_TENSOR_MAP_FLOAT_OOB_FILL_NONE);
    return tm;
}

#define AB_GRID 24
#define G4_GRID 12
__device__ __align__(1024) bf16 g_qkvA[2048 * 1536];
__device__ __align__(1024) bf16 g_oA[2048 * 512];
__device__ __align__(1024) bf16 g_qkvB[2048 * 12288];
__device__ __align__(1024) bf16 g_kvmem[64 * 8 * 8192];
__device__ __align__(1024) bf16 g_oB[2048 * 4096];
__device__ __align__(1024) float g_part[2 * 64 * 256];
__device__ __align__(1024) float g_part_fb[2 * 64 * 32 * 64];
__device__ __align__(1024) uint4 g_membuf_fb[64 * 512];
__device__ __align__(128) unsigned int g_flags[4096];

__global__ void cleanup_kernel(int fallback) {
    const int i = blockIdx.x * blockDim.x + threadIdx.x;
    const int n = gridDim.x * blockDim.x;
    uint4 z = make_uint4(0, 0, 0, 0);
    for (int k = i; k < 2 * 64 * 64; k += n) reinterpret_cast<uint4*>(g_part)[k] = z;
    if (i < 4096) g_flags[i] = 0u;
    if (fallback) {
        for (int k = i; k < 2 * 64 * 32 * 16; k += n) reinterpret_cast<uint4*>(g_part_fb)[k] = z;
        for (int k = i; k < 64 * 512; k += n) g_membuf_fb[k] = z;
    }
}

__global__ void delay_kernel() {}

template <typename T> static T* sym_addr(T& sym) { void* p = nullptr; cudaGetSymbolAddress(&p, sym); return (T*)p; }

extern "C" void kernel_launch(void* const* d_in, const int* in_sizes, int n_in, void* d_out, int out_size) {
    const bf16* A_x = (const bf16*)d_in[0];
    const bf16* A_wqkv = (const bf16*)d_in[1];
    const bf16* A_wo = (const bf16*)d_in[2];
    const bf16* B_x = (const bf16*)d_in[3];
    const bf16* B_mem0 = (const bf16*)d_in[4];
    const bf16* B_Wq = (const bf16*)d_in[5];
    const bf16* B_Wk = (const bf16*)d_in[6];
    const bf16* B_Wv = (const bf16*)d_in[7];
    const bf16* B_Wo = (const bf16*)d_in[8];
    bf16* out = (bf16*)d_out;

    static bool inited = false;
    static bool use_fb = false;
    static cudaStream_t s1, s2, s3, s4;
    static cudaEvent_t e_kv, e_s1, e_ch, e_q, e_s3, e_s4;
    if (!inited) {
        init_encode();
        cudaFuncSetAttribute(gemm_w_kernel, cudaFuncAttributeMaxDynamicSharedMemorySize, GW_SMEM);
        cudaFuncSetAttribute(gemm_s_kernel, cudaFuncAttributeMaxDynamicSharedMemorySize, GS_SMEM);
        cudaFuncSetAttribute(chain_kernel, cudaFuncAttributeMaxDynamicSharedMemorySize, CH_SMEM);
        cudaFuncSetAttribute(chain_kernel, cudaFuncAttributeNonPortableClusterSizeAllowed, 1);
        cudaFuncSetAttribute(chain_fb_kernel, cudaFuncAttributeMaxDynamicSharedMemorySize, CF_SMEM);
        {
            cudaLaunchConfig_t cfg = {};
            cfg.gridDim = dim3(64); cfg.blockDim = dim3(384); cfg.dynamicSmemBytes = CH_SMEM;
            cudaLaunchAttribute at[1];
            at[0].id = cudaLaunchAttributeClusterDimension; at[0].val.clusterDim.x = 16; at[0].val.clusterDim.y = 1; at[0].val.clusterDim.z = 1;
            cfg.attrs = at; cfg.numAttrs = 1;
            int ncl = 0;
            cudaError_t e = cudaOccupancyMaxActiveClusters(&ncl, chain_kernel, &cfg);
            if (e != cudaSuccess || ncl < 4) use_fb = true;
            (void)cudaGetLastError();
        }
        cudaFuncSetAttribute(attn_a_kernel, cudaFuncAttributeMaxDynamicSharedMemorySize, AA_SMEM);
        cudaFuncSetAttribute(attn_b_kernel, cudaFuncAttributeMaxDynamicSharedMemorySize, AB_SMEM);
        int plo = 0, phi = 0;
        cudaDeviceGetStreamPriorityRange(&plo, &phi);
        cudaStreamCreateWithPriority(&s1, cudaStreamNonBlocking, plo);
        cudaStreamCreateWithPriority(&s2, cudaStreamNonBlocking, phi);
        cudaStreamCreateWithPriority(&s3, cudaStreamNonBlocking, phi);
        cudaStreamCreateWithPriority(&s4, cudaStreamNonBlocking, phi);
        cudaEventCreateWithFlags(&e_kv, cudaEventDisableTiming);
        cudaEventCreateWithFlags(&e_s1, cudaEventDisableTiming);
        cudaEventCreateWithFlags(&e_ch, cudaEventDisableTiming);
        cudaEventCreateWithFlags(&e_q, cudaEventDisableTiming);
        cudaEventCreateWithFlags(&e_s3, cudaEventDisableTiming);
        cudaEventCreateWithFlags(&e_s4, cudaEventDisableTiming);
        inited = true;
    }
    void *qkvA, *oA, *qkvB, *kvmem, *oB, *part, *membuf, *flags;
    cudaGetSymbolAddress(&qkvA, g_qkvA); cudaGetSymbolAddress(&oA, g_oA); cudaGetSymbolAddress(&qkvB, g_qkvB);
    cudaGetSymbolAddress(&kvmem, g_kvmem); cudaGetSymbolAddress(&oB, g_oB); cudaGetSymbolAddress(&part, g_part);
    membuf = nullptr; cudaGetSymbolAddress(&flags, g_flags);
    cudaStream_t s0 = cudaStreamPerThread;

    cudaEventRecord(e_kv, s0);
    cudaStreamWaitEvent(s1, e_kv, 0);
    cudaStreamWaitEvent(s2, e_kv, 0);
    ChainParams pc;
    pc.tmW[0] = make_tmap_3d64(B_Wq, 512, 4096, 4096, 256, 1);
    pc.tmW[1] = make_tmap_3d64(B_Wk, 512, 4096, 4096, 256, 1);
    pc.tmW[2] = make_tmap_3d64(B_Wv, 512, 4096, 4096, 256, 1);
    pc.tmWo = make_tmap_3d64(B_Wo, 4096, 512, 512, 128, 1);
    pc.tmKV = make_tmap_3d64(qkvB, 2048, 12288, 12288, 32, 1);
    pc.mem0 = B_mem0; pc.kvmem = (bf16*)kvmem; pc.part = (float*)part; pc.membuf = (uint4*)membuf;
    pc.flags = (const unsigned int*)flags; pc.flag_target = 128; pc.dbg = nullptr; pc.seg_flags = (unsigned int*)flags + 1024;
    if (!use_fb) {
        cudaLaunchConfig_t cfg = {};
        cfg.gridDim = dim3(64); cfg.blockDim = dim3(384); cfg.dynamicSmemBytes = CH_SMEM; cfg.stream = s2;
        cudaLaunchAttribute at[2];
        at[0].id = cudaLaunchAttributeClusterDimension; at[0].val.clusterDim.x = 16; at[0].val.clusterDim.y = 1; at[0].val.clusterDim.z = 1;
        cfg.attrs = at; cfg.numAttrs = 1;
        cudaLaunchKernelEx(&cfg, chain_kernel, pc);
    }

    else {
        ChainFbParams pf;
        for (int i = 0; i < 3; i++) pf.tmW[i] = pc.tmW[i];
        pf.tmWo = pc.tmWo; pf.tmKV = pc.tmKV; pf.mem0 = pc.mem0; pf.kvmem = pc.kvmem;
        void *pfb, *mfb;
        cudaGetSymbolAddress(&pfb, g_part_fb); cudaGetSymbolAddress(&mfb, g_membuf_fb);
        pf.part = (float*)pfb; pf.membuf = (uint4*)mfb; pf.flags = pc.flags; pf.flag_target = pc.flag_target; pf.seg_flags = pc.seg_flags; pf.dbg = nullptr;
        cudaLaunchConfig_t cfg = {};
        cfg.gridDim = dim3(64); cfg.blockDim = dim3(384); cfg.dynamicSmemBytes = CF_SMEM; cfg.stream = s2;
        cudaLaunchAttribute at[1];
        at[0].id = cudaLaunchAttributeClusterDimension; at[0].val.clusterDim.x = 2; at[0].val.clusterDim.y = 1; at[0].val.clusterDim.z = 1;
        cfg.attrs = at; cfg.numAttrs = 1;
        cudaLaunchKernelEx(&cfg, chain_fb_kernel, pf);
    }
    cudaEventRecord(e_ch, s2);
    delay_kernel<<<1, 32, 0, s1>>>();
    GemmWParams pkv;
    pkv.tmA = make_tmap_3d64(B_x, 2048, 512, 512, 128, 1);
    pkv.tmB[0] = make_tmap_3d64(B_Wk, 512, 4096, 4096, 64, 2);
    pkv.tmB[1] = make_tmap_3d64(B_Wv, 512, 4096, 4096, 64, 2);
    pkv.tmB[2] = make_tmap_3d64(B_Wq, 512, 4096, 4096, 64, 2);
    pkv.tmC = make_tmap_3d64(qkvB, 2048, 12288, 12288, 128, 1);
    pkv.ntiles_per_mat = 32; pkv.c_col64[0] = 64; pkv.c_col64[1] = 128; pkv.c_col64[2] = 0;
    pkv.m_splits = 1; pkv.mtiles_per_cta = 16; pkv.flag_mats = 2; pkv.flags = (unsigned int*)flags; pkv.tl_id = 1;
    gemm_w_kernel<<<64, 384, GW_SMEM, s1>>>(pkv);

    GemmWParams pq = pkv;
    pq.tmB[0] = pkv.tmB[2]; pq.c_col64[0] = 0; pq.m_splits = 2; pq.mtiles_per_cta = 8; pq.flag_mats = 0; pq.flags = nullptr; pq.tl_id = 2;
    gemm_w_kernel<<<64, 384, GW_SMEM, s1>>>(pq);
    cudaEventRecord(e_q, s1);
    cudaStreamWaitEvent(s3, e_q, 0);
    cudaStreamWaitEvent(s4, e_q, 0);
    AttnBParams pb;
    pb.tmQKV = make_tmap_3d64(qkvB, 2048, 12288, 12288, 32, 1);
    pb.tmKVM = make_tmap_3d64(kvmem, 512, 8192, 8192, 8, 1);
    pb.tmO = make_tmap_3d64(oB, 2048, 4096, 4096, 32, 1);
    pb.seg_flags = (const unsigned int*)flags + 1024; pb.seg_target = 64; pb.tile_flags = (unsigned int*)flags + 64;
    attn_b_kernel<<<AB_GRID, 128, AB_SMEM, s3>>>(pb);
    cudaEventRecord(e_s3, s3);

    GemmSParams p4;
    p4.tmA = make_tmap_3d64(oB, 2048, 4096, 4096, 128, 1);
    p4.tmB = make_tmap_3d64(B_Wo, 4096, 512, 512, 64, 2);
    p4.tmC = make_tmap_3d64(out, 2048, 1024, 1024, 64, 1);
    p4.n_tiles = 4; p4.m_tiles = 16; p4.c = out; p4.ldc = 1024; p4.kblocks_half = 32; p4.c_col64 = 8;
    p4.tile_flags = (const unsigned int*)flags + 64; p4.tile_target = 128;
    {
        cudaLaunchConfig_t cfg = {};
        cfg.gridDim = dim3(G4_GRID); cfg.blockDim = dim3(288); cfg.dynamicSmemBytes = GS_SMEM; cfg.stream = s4;
        cudaLaunchAttribute at[2];
        at[0].id = cudaLaunchAttributeClusterDimension; at[0].val.clusterDim.x = 2; at[0].val.clusterDim.y = 1; at[0].val.clusterDim.z = 1;
        cfg.attrs = at; cfg.numAttrs = 1;
        cudaLaunchKernelEx(&cfg, gemm_s_kernel, p4);
    }
    cudaEventRecord(e_s4, s4);

    GemmWParams p1;
    p1.tmA = make_tmap_3d64(A_x, 2048, 512, 512, 128, 1);
    p1.tmB[0] = make_tmap_3d64(A_wqkv, 512, 1536, 1536, 64, 2); p1.tmB[1] = p1.tmB[0]; p1.tmB[2] = p1.tmB[0];
    p1.tmC = make_tmap_3d64(qkvA, 2048, 1536, 1536, 128, 1);
    p1.ntiles_per_mat = 12; p1.c_col64[0] = p1.c_col64[1] = p1.c_col64[2] = 0;
    p1.m_splits = 4; p1.mtiles_per_cta = 4; p1.flag_mats = 0; p1.flags = nullptr; p1.tl_id = 3;
    gemm_w_kernel<<<48, 384, GW_SMEM, s1>>>(p1);

    AttnAParams pa;
    {
        cuuint64_t dims[2] = {1536, 2048}; cuuint64_t strides[1] = {3072}; cuuint32_t box[2] = {16, AA_KT}; cuuint32_t es[2] = {1, 1};
        g_encode(&pa.tmKV, CU_TENSOR_MAP_DATA_TYPE_BFLOAT16, 2, qkvA, dims, strides, box, es, CU_TENSOR_MAP_INTERLEAVE_NONE,
                 CU_TENSOR_MAP_SWIZZLE_32B, CU_TENSOR_MAP_L2_PROMOTION_L2_128B, CU_TENSOR_MAP_FLOAT_OOB_FILL_NONE);
    }
    pa.qkv = (const bf16*)qkvA; pa.o = (bf16*)oA;
    attn_a_kernel<<<256, 256, AA_SMEM, s1>>>(pa);

    GemmWParams p2;
    p2.tmA = make_tmap_3d64(oA, 2048, 512, 512, 128, 1);
    p2.tmB[0] = make_tmap_3d64(A_wo, 512, 512, 512, 64, 2); p2.tmB[1] = p2.tmB[0]; p2.tmB[2] = p2.tmB[0];
    p2.tmC = make_tmap_3d64(out, 2048, 1024, 1024, 128, 1);
    p2.ntiles_per_mat = 4; p2.c_col64[0] = p2.c_col64[1] = p2.c_col64[2] = 0;
    p2.m_splits = 16; p2.mtiles_per_cta = 1; p2.flag_mats = 0; p2.flags = nullptr; p2.tl_id = 5;
    gemm_w_kernel<<<64, 384, GW_SMEM, s1>>>(p2);

    cudaEventRecord(e_s1, s1);
    cudaStreamWaitEvent(s0, e_s1, 0);
    cudaStreamWaitEvent(s0, e_ch, 0);
    cudaStreamWaitEvent(s0, e_s3, 0);
    cudaStreamWaitEvent(s0, e_s4, 0);
    cleanup_kernel<<<64, 256, 0, s0>>>(use_fb ? 1 : 0);
}
```
